```python
import torch

def _softmax(x, axis=-1):
    return torch.softmax(x, dim=axis)
def _gelu(x):
    return torch.nn.functional.gelu(x, approximate="tanh")
def _silu(x):
    return torch.nn.functional.silu(x)
def _sigmoid(x):
    return torch.sigmoid(x)
def _layernorm(x, axis=-1, eps=1e-5):
    m = x.mean(dim=axis, keepdim=True)
    v = x.var(dim=axis, keepdim=True, unbiased=False)
    return (x - m) / torch.sqrt(v + eps)
def _scatter_add(tgt, idx, src, axis=0):
    return tgt.clone().index_add_(axis, idx, src)
def _segment_sum(src, seg, n):
    out = torch.zeros((n,) + src.shape[1:], dtype=src.dtype)
    return out.index_add_(0, seg, src)
def _pad(x, pw):
    flat = tuple(v for pair in reversed(pw) for v in pair)
    return torch.nn.functional.pad(x, flat)

kernel_name = 'interleave_layers__linear_kernel_hedgehog__mixer_token_mlp__prompt'

def setup_inputs():

    _w = (lambda a: (lambda t: t.to(torch.bfloat16) if t.is_floating_point() else t)(torch.as_tensor(a)))
    def _A_setup():
        B, S, D, H = 1, 2048, 640, 32
        Dh = D // H
        return {
            "x": _w((lambda *s: torch.randn(*s, dtype=torch.bfloat16) * 0.05)(B, S, D)),
            "wqkv": _w((lambda *s: torch.randn(*s, dtype=torch.bfloat16) * 0.4)(D, 3 * D)),
            "w_phi": _w((lambda *s: torch.randn(*s, dtype=torch.bfloat16) * 0.4)(H, Dh, Dh) * (Dh ** -0.5)),
            "wo": _w((lambda *s: torch.randn(*s, dtype=torch.bfloat16) * 0.05)(D, D)),
        }
    _A_in = _A_setup()

    def _B_setup():
        B, S, D, F = 1, 2048, 640, 1536
        return {
            "x": _w((lambda *s: torch.randn(*s, dtype=torch.bfloat16) * 0.05)(B, S, D)),
            "w1": _w((lambda *s: torch.randn(*s, dtype=torch.bfloat16) * 0.8)(S, F) * (S ** -0.5)),
            "b1": _w((lambda *s: torch.randn(*s, dtype=torch.bfloat16) * 0.8)(F) * 0.02),
            "w2": _w((lambda *s: torch.randn(*s, dtype=torch.bfloat16) * 0.8)(F, S) * (F ** -0.5)),
            "b2": _w((lambda *s: torch.randn(*s, dtype=torch.bfloat16) * 0.8)(S) * 0.02),
        }
    _B_in = _B_setup()

    return {
        "A_x": _A_in["x"],
        "A_wqkv": _A_in["wqkv"],
        "A_w_phi": _A_in["w_phi"],
        "A_wo": _A_in["wo"],
        "B_x": _B_in["x"],
        "B_w1": _B_in["w1"],
        "B_b1": _B_in["b1"],
        "B_w2": _B_in["w2"],
        "B_b2": _B_in["b2"],
    }

def reference(A_x, A_wqkv, A_w_phi, A_wo, B_x, B_w1, B_b1, B_w2, B_b2):
    def _A_ref(x, wqkv, w_phi, wo):
        B, S, D = x.shape
        H = 32; Dh = D // H
        qkv = (lambda x, *d: x.permute(*d))((x @ wqkv).reshape(B, S, 3, H, Dh), 2, 0, 3, 1, 4)
        q, k, v = qkv[0], qkv[1], qkv[2]
        pq = torch.einsum("bhsd,hdf->bhsf", q, w_phi)
        pk = torch.einsum("bhsd,hdf->bhsf", k, w_phi)
        phi_q = torch.concatenate([_softmax(pq, axis=-1), _softmax(-pq, axis=-1)], axis=-1)
        phi_k = torch.concatenate([_softmax(pk, axis=-1), _softmax(-pk, axis=-1)], axis=-1)
        kv = torch.einsum("bhsf,bhsd->bhfd", phi_k, v)
        z  = torch.einsum("bhsf->bhf", phi_k)
        num = torch.einsum("bhqf,bhfd->bhqd", phi_q, kv)
        den = torch.einsum("bhqf,bhf->bhq", phi_q, z)[..., None] + 1e-6
        o = num / den
        return (lambda x, *d: x.permute(*d))(o, 0, 2, 1, 3).reshape(B, S, D) @ wo

    def _B_ref(x, w1, b1, w2, b2):
        B, S, D = x.shape
        h = _layernorm(x, axis=-1)
        u = torch.einsum("bsd,sf->bdf", h, w1) + b1
        u = _gelu(u)
        y = torch.einsum("bdf,fs->bds", u, w2) + b2
        return (lambda x, *d: x.permute(*d))(y, 0, 2, 1)

    x = A_x
    x = x + _A_ref(_layernorm(x, axis=-1), A_wqkv, A_w_phi, A_wo)
    x = x + _B_ref(_layernorm(x, axis=-1), B_w1, B_b1, B_w2, B_b2)
    x = x + _A_ref(_layernorm(x, axis=-1), A_wqkv, A_w_phi, A_wo)
    x = x + _B_ref(_layernorm(x, axis=-1), B_w1, B_b1, B_w2, B_b2)
    return x
```

```cpp
#include <cuda_runtime.h>
#include <cuda_bf16.h>
#include <cuda.h>
#include <stdint.h>

namespace {

constexpr int S_ = 2048, D_ = 640, F_ = 1536;
constexpr int NCTA = 128;
constexpr int NTHREADS = 384;

__device__ __align__(1024) __nv_bfloat16 g_wts[2560 * 640];
__device__ __align__(1024) __nv_bfloat16 g_act[3 * 2048 * 640];
__device__ __align__(1024) __nv_bfloat16 g_u[640 * 1536];
__device__ __align__(16) float g_colsum[1920];
__device__ __align__(16) float2 g_stats[2][2048 * 8];
__device__ __align__(16) float g_kv[2][32 * 840];
__device__ __align__(16) uint4 g_ll[2][2048 * 8];
constexpr int C_P0 = 0, C_KV = 1, C_O = C_KV + 16, C_H = C_O + 32, C_U = C_H + 32, C_X = C_U + 10, C_NUM = C_X + 16;
__device__ __align__(128) unsigned g_cnt[C_NUM * 32];
__device__ unsigned g_epoch;

constexpr int KB = 1024;
constexpr int SM_MISC = 224 * KB;
constexpr int SM_BARS = SM_MISC;
constexpr int SM_CS = SM_MISC + 1280;
constexpr int SM_P0 = SM_CS + 960;
constexpr int SM_TOTAL = 227 * KB;
constexpr int P1_NA = 5, P1_NB = 8, P1_A = 0, P1_B = 80 * KB, P1_STG = 160 * KB;
constexpr int P3_NA = 7, P3_NB = 10, P3_B = 0, P3_A = 100 * KB;
constexpr int P4_NA = 8, P4_NB = 12, P4_B = 0, P4_A = 96 * KB;
constexpr int P5_NA = 9, P5_NB = 8, P5_A = 0, P5_B = 144 * KB;
constexpr int B_P1A = 0, B_P1B = B_P1A + P1_NA, B_P3A = B_P1B + P1_NB, B_P3B = B_P3A + P3_NA, B_P4A = B_P3B + P3_NB,
              B_P4B = B_P4A + P4_NA, B_P5A = B_P4B + P4_NB, B_P5B = B_P5A + P5_NA, B_NRING = B_P5B + P5_NB;
constexpr int B_EMPTY = 68;
constexpr int B_MLDONE = 136, B_KVRDY = 137;

__device__ __forceinline__ uint32_t smem_u32(const void* p) { return (uint32_t)__cvta_generic_to_shared(p); }
__device__ __forceinline__ void mbar_init(uint32_t a, int c) { asm volatile("mbarrier.init.shared::cta.b64 [%0], %1;" ::"r"(a), "r"(c)); }
__device__ __forceinline__ void mbar_expect(uint32_t a, int bytes) {
  asm volatile("mbarrier.arrive.expect_tx.shared::cta.b64 _, [%0], %1;" ::"r"(a), "r"(bytes) : "memory");
}
__device__ __forceinline__ void mbar_arrive(uint32_t a) { asm volatile("mbarrier.arrive.shared::cta.b64 _, [%0];" ::"r"(a) : "memory"); }
__device__ __forceinline__ bool mbar_try(uint32_t a, uint32_t ph) {
  uint32_t ok;
  asm volatile("{\n.reg .pred p;\nmbarrier.try_wait.parity.shared::cta.b64 p, [%1], %2;\nselp.u32 %0, 1, 0, p;\n}" : "=r"(ok) : "r"(a), "r"(ph) : "memory");
  return ok;
}
__device__ __forceinline__ void mbar_wait(uint32_t a, uint32_t ph) {
  if (mbar_try(a, ph)) return;
  int n = 0;
  while (!mbar_try(a, ph)) { if (++n > (1 << 22)) __trap(); }
}
__device__ __forceinline__ void tma2d(uint32_t dst, const CUtensorMap* m, int c0, int c1, uint32_t bar) {
  asm volatile("cp.async.bulk.tensor.2d.shared::cluster.global.mbarrier::complete_tx::bytes [%0], [%1, {%3, %4}], [%2];"
               ::"r"(dst), "l"(m), "r"(bar), "r"(c0), "r"(c1) : "memory");
}
__device__ __forceinline__ void l2_prefetch(const void* p, int bytes) {
  asm volatile("cp.async.bulk.prefetch.L2.global [%0], %1;" ::"l"(p), "r"(bytes) : "memory");
}
__device__ __forceinline__ unsigned ld_acq(const unsigned* p) {
  unsigned v; asm volatile("ld.acquire.gpu.global.u32 %0, [%1];" : "=r"(v) : "l"(p) : "memory"); return v;
}
__device__ __forceinline__ void red_rel(unsigned* p) { asm volatile("red.release.gpu.global.add.u32 [%0], 1;" ::"l"(p) : "memory"); }
__device__ __forceinline__ void wait_cnt(int idx, unsigned target) {
  const unsigned* p = &g_cnt[idx * 32];
  int n = 0;
  while ((int)(ld_acq(p) - target) < 0) { if (++n > (1 << 21)) __trap(); }
}
__device__ __forceinline__ void fence_async_global() { asm volatile("fence.proxy.async.global;" ::: "memory"); }
__device__ __forceinline__ void fence_async_smem() { asm volatile("fence.proxy.async.shared::cta;" ::: "memory"); }
__device__ __forceinline__ void bar_sync(int id, int n) { asm volatile("bar.sync %0, %1;" ::"r"(id), "r"(n) : "memory"); }
__device__ __forceinline__ void bar_arrive(int id, int n) { asm volatile("bar.arrive %0, %1;" ::"r"(id), "r"(n) : "memory"); }
__device__ __forceinline__ void wg_fence() { asm volatile("wgmma.fence.sync.aligned;" ::: "memory"); }
__device__ __forceinline__ void wg_commit() { asm volatile("wgmma.commit_group.sync.aligned;" ::: "memory"); }
template <int N> __device__ __forceinline__ void wg_wait() { asm volatile("wgmma.wait_group.sync.aligned %0;" ::"n"(N) : "memory"); }
__device__ __forceinline__ uint64_t mkdesc(uint32_t addr, uint32_t lbo, uint32_t sbo) {
  return (uint64_t)((addr & 0x3FFFF) >> 4) | ((uint64_t)(lbo >> 4) << 16) | ((uint64_t)(sbo >> 4) << 32) | (1ull << 62);
}
__device__ __forceinline__ uint32_t pack2(float lo, float hi) {
  uint32_t r; asm("cvt.rn.bf16x2.f32 %0, %1, %2;" : "=r"(r) : "f"(hi), "f"(lo)); return r;
}
__device__ __forceinline__ float lo_f(uint32_t v) { return __uint_as_float(v << 16); }
__device__ __forceinline__ float hi_f(uint32_t v) { return __uint_as_float(v & 0xffff0000u); }
__device__ __forceinline__ float ex2(float x) { float r; asm("ex2.approx.ftz.f32 %0, %1;" : "=f"(r) : "f"(x)); return r; }
__device__ __forceinline__ float rcp(float x) { float r; asm("rcp.approx.ftz.f32 %0, %1;" : "=f"(r) : "f"(x)); return r; }
__device__ __forceinline__ float tanh_a(float x) { float r; asm("tanh.approx.f32 %0, %1;" : "=f"(r) : "f"(x)); return r; }
__device__ __forceinline__ void sts128(uint32_t a, uint32_t x, uint32_t y, uint32_t z, uint32_t w) {
  asm volatile("st.shared.v4.b32 [%0], {%1, %2, %3, %4};" ::"r"(a), "r"(x), "r"(y), "r"(z), "r"(w) : "memory");
}
__device__ __forceinline__ float2 lds64f(uint32_t a) {
  float2 v; asm volatile("ld.shared.v2.f32 {%0, %1}, [%2];" : "=f"(v.x), "=f"(v.y) : "r"(a)); return v;
}
__device__ __forceinline__ void red_add2(float* p, float a, float b) {
  asm volatile("red.relaxed.gpu.global.add.v2.f32 [%0], {%1, %2};" ::"l"(p), "f"(a), "f"(b) : "memory");
}
__device__ __forceinline__ uint4 ld_vol4(const uint4* p) {
  uint4 v; asm volatile("ld.relaxed.gpu.global.v4.u32 {%0, %1, %2, %3}, [%4];" : "=r"(v.x), "=r"(v.y), "=r"(v.z), "=r"(v.w) : "l"(p) : "memory"); return v;
}
__device__ __forceinline__ void st_vol4(uint4* p, uint4 v) {
  asm volatile("st.relaxed.gpu.global.v4.u32 [%0], {%1, %2, %3, %4};" ::"l"(p), "r"(v.x), "r"(v.y), "r"(v.z), "r"(v.w) : "memory");
}
__device__ __forceinline__ void mma16816(float (&c)[4], const uint32_t (&a)[4], uint32_t b0, uint32_t b1) {
  asm volatile("mma.sync.aligned.m16n8k16.row.col.f32.bf16.bf16.f32 {%0,%1,%2,%3}, {%4,%5,%6,%7}, {%8,%9}, {%0,%1,%2,%3};"
               : "+f"(c[0]), "+f"(c[1]), "+f"(c[2]), "+f"(c[3]) : "r"(a[0]), "r"(a[1]), "r"(a[2]), "r"(a[3]), "r"(b0), "r"(b1));
}
__device__ __forceinline__ float quad_sum(float v) {
  v += __shfl_xor_sync(0xffffffffu, v, 1);
  v += __shfl_xor_sync(0xffffffffu, v, 2);
  return v;
}
template<int TA, int TB> __device__ __forceinline__ void wgmma_ss_n64(float (&d)[32], uint64_t da, uint64_t db, int sd) {
  asm volatile("{\n.reg .pred p;\nsetp.ne.b32 p, %34, 0;\n"
    "wgmma.mma_async.sync.aligned.m64n64k16.f32.bf16.bf16 "
    "{%0, %1, %2, %3, %4, %5, %6, %7, %8, %9, %10, %11, %12, %13, %14, %15, %16, %17, %18, %19, %20, %21, %22, %23, %24, %25, %26, %27, %28, %29, %30, %31}, %32, %33, p, 1, 1, %35, %36;\n}\n"
    : "+f"(d[0]), "+f"(d[1]), "+f"(d[2]), "+f"(d[3]), "+f"(d[4]), "+f"(d[5]), "+f"(d[6]), "+f"(d[7]), "+f"(d[8]), "+f"(d[9]), "+f"(d[10]), "+f"(d[11]), "+f"(d[12]), "+f"(d[13]), "+f"(d[14]), "+f"(d[15]), "+f"(d[16]), "+f"(d[17]), "+f"(d[18]), "+f"(d[19]), "+f"(d[20]), "+f"(d[21]), "+f"(d[22]), "+f"(d[23]), "+f"(d[24]), "+f"(d[25]), "+f"(d[26]), "+f"(d[27]), "+f"(d[28]), "+f"(d[29]), "+f"(d[30]), "+f"(d[31])
    : "l"(da), "l"(db), "r"(sd), "n"(TA), "n"(TB));
}
template<int TA, int TB> __device__ __forceinline__ void wgmma_ss_n80(float (&d)[40], uint64_t da, uint64_t db, int sd) {
  asm volatile("{\n.reg .pred p;\nsetp.ne.b32 p, %42, 0;\n"
    "wgmma.mma_async.sync.aligned.m64n80k16.f32.bf16.bf16 "
    "{%0, %1, %2, %3, %4, %5, %6, %7, %8, %9, %10, %11, %12, %13, %14, %15, %16, %17, %18, %19, %20, %21, %22, %23, %24, %25, %26, %27, %28, %29, %30, %31, %32, %33, %34, %35, %36, %37, %38, %39}, %40, %41, p, 1, 1, %43, %44;\n}\n"
    : "+f"(d[0]), "+f"(d[1]), "+f"(d[2]), "+f"(d[3]), "+f"(d[4]), "+f"(d[5]), "+f"(d[6]), "+f"(d[7]), "+f"(d[8]), "+f"(d[9]), "+f"(d[10]), "+f"(d[11]), "+f"(d[12]), "+f"(d[13]), "+f"(d[14]), "+f"(d[15]), "+f"(d[16]), "+f"(d[17]), "+f"(d[18]), "+f"(d[19]), "+f"(d[20]), "+f"(d[21]), "+f"(d[22]), "+f"(d[23]), "+f"(d[24]), "+f"(d[25]), "+f"(d[26]), "+f"(d[27]), "+f"(d[28]), "+f"(d[29]), "+f"(d[30]), "+f"(d[31]), "+f"(d[32]), "+f"(d[33]), "+f"(d[34]), "+f"(d[35]), "+f"(d[36]), "+f"(d[37]), "+f"(d[38]), "+f"(d[39])
    : "l"(da), "l"(db), "r"(sd), "n"(TA), "n"(TB));
}
template<int TA, int TB> __device__ __forceinline__ void wgmma_ss_n160(float (&d)[80], uint64_t da, uint64_t db, int sd) {
  asm volatile("{\n.reg .pred p;\nsetp.ne.b32 p, %82, 0;\n"
    "wgmma.mma_async.sync.aligned.m64n160k16.f32.bf16.bf16 "
    "{%0, %1, %2, %3, %4, %5, %6, %7, %8, %9, %10, %11, %12, %13, %14, %15, %16, %17, %18, %19, %20, %21, %22, %23, %24, %25, %26, %27, %28, %29, %30, %31, %32, %33, %34, %35, %36, %37, %38, %39, %40, %41, %42, %43, %44, %45, %46, %47, %48, %49, %50, %51, %52, %53, %54, %55, %56, %57, %58, %59, %60, %61, %62, %63, %64, %65, %66, %67, %68, %69, %70, %71, %72, %73, %74, %75, %76, %77, %78, %79}, %80, %81, p, 1, 1, %83, %84;\n}\n"
    : "+f"(d[0]), "+f"(d[1]), "+f"(d[2]), "+f"(d[3]), "+f"(d[4]), "+f"(d[5]), "+f"(d[6]), "+f"(d[7]), "+f"(d[8]), "+f"(d[9]), "+f"(d[10]), "+f"(d[11]), "+f"(d[12]), "+f"(d[13]), "+f"(d[14]), "+f"(d[15]), "+f"(d[16]), "+f"(d[17]), "+f"(d[18]), "+f"(d[19]), "+f"(d[20]), "+f"(d[21]), "+f"(d[22]), "+f"(d[23]), "+f"(d[24]), "+f"(d[25]), "+f"(d[26]), "+f"(d[27]), "+f"(d[28]), "+f"(d[29]), "+f"(d[30]), "+f"(d[31]), "+f"(d[32]), "+f"(d[33]), "+f"(d[34]), "+f"(d[35]), "+f"(d[36]), "+f"(d[37]), "+f"(d[38]), "+f"(d[39]), "+f"(d[40]), "+f"(d[41]), "+f"(d[42]), "+f"(d[43]), "+f"(d[44]), "+f"(d[45]), "+f"(d[46]), "+f"(d[47]), "+f"(d[48]), "+f"(d[49]), "+f"(d[50]), "+f"(d[51]), "+f"(d[52]), "+f"(d[53]), "+f"(d[54]), "+f"(d[55]), "+f"(d[56]), "+f"(d[57]), "+f"(d[58]), "+f"(d[59]), "+f"(d[60]), "+f"(d[61]), "+f"(d[62]), "+f"(d[63]), "+f"(d[64]), "+f"(d[65]), "+f"(d[66]), "+f"(d[67]), "+f"(d[68]), "+f"(d[69]), "+f"(d[70]), "+f"(d[71]), "+f"(d[72]), "+f"(d[73]), "+f"(d[74]), "+f"(d[75]), "+f"(d[76]), "+f"(d[77]), "+f"(d[78]), "+f"(d[79])
    : "l"(da), "l"(db), "r"(sd), "n"(TA), "n"(TB));
}
template<int TB> __device__ __forceinline__ void wgmma_rs_n88(float (&d)[44], const uint32_t (&a)[4], uint64_t db, int sd) {
  asm volatile("{\n.reg .pred p;\nsetp.ne.b32 p, %49, 0;\n"
    "wgmma.mma_async.sync.aligned.m64n88k16.f32.bf16.bf16 "
    "{%0, %1, %2, %3, %4, %5, %6, %7, %8, %9, %10, %11, %12, %13, %14, %15, %16, %17, %18, %19, %20, %21, %22, %23, %24, %25, %26, %27, %28, %29, %30, %31, %32, %33, %34, %35, %36, %37, %38, %39, %40, %41, %42, %43}, {%44, %45, %46, %47}, %48, p, 1, 1, %50;\n}\n"
    : "+f"(d[0]), "+f"(d[1]), "+f"(d[2]), "+f"(d[3]), "+f"(d[4]), "+f"(d[5]), "+f"(d[6]), "+f"(d[7]), "+f"(d[8]), "+f"(d[9]), "+f"(d[10]), "+f"(d[11]), "+f"(d[12]), "+f"(d[13]), "+f"(d[14]), "+f"(d[15]), "+f"(d[16]), "+f"(d[17]), "+f"(d[18]), "+f"(d[19]), "+f"(d[20]), "+f"(d[21]), "+f"(d[22]), "+f"(d[23]), "+f"(d[24]), "+f"(d[25]), "+f"(d[26]), "+f"(d[27]), "+f"(d[28]), "+f"(d[29]), "+f"(d[30]), "+f"(d[31]), "+f"(d[32]), "+f"(d[33]), "+f"(d[34]), "+f"(d[35]), "+f"(d[36]), "+f"(d[37]), "+f"(d[38]), "+f"(d[39]), "+f"(d[40]), "+f"(d[41]), "+f"(d[42]), "+f"(d[43])
    : "r"(a[0]), "r"(a[1]), "r"(a[2]), "r"(a[3]), "l"(db), "r"(sd), "n"(TB));
}

template <int N> struct Pos {
  int slot = 0; uint32_t ph = 0;
  __device__ __forceinline__ void next() { if (++slot == N) { slot = 0; ph ^= 1; } }
};

template <int N> __device__ __forceinline__ void zero(float (&a)[N]) {
#pragma unroll
  for (int i = 0; i < N; i++) a[i] = 0.f;
}

struct Params {
  const __nv_bfloat16 *x, *wqkv, *wphi, *wo, *w1, *b1, *w2, *b2;
  __nv_bfloat16* out;
};

constexpr int BAR_CONS = 1, BAR_SIG = 2, BAR_SIG2 = 3;
constexpr float LOG2E = 1.4426950408889634f;

__device__ __forceinline__ float2 chunk_stats(const uint32_t (&v)[10]) {
  float s = 0.f;
#pragma unroll
  for (int i = 0; i < 10; i++) s += lo_f(v[i]) + hi_f(v[i]);
  s = quad_sum(s);
  float mean = s * (1.f / 80.f);
  float q = 0.f;
#pragma unroll
  for (int i = 0; i < 10; i++) { float a = lo_f(v[i]) - mean, b = hi_f(v[i]) - mean; q += a * a; q += b * b; }
  q = quad_sum(q);
  return make_float2(mean, q);
}
__device__ __forceinline__ float2 combine_stats(float m0, float q0, float m1, float q1) {
  float mean = quad_sum(m0 + m1) * 0.125f;
  float d0 = m0 - mean, d1 = m1 - mean;
  float q = quad_sum(q0 + q1 + 80.f * (d0 * d0 + d1 * d1));
  return make_float2(mean, q * (1.f / 640.f));
}

__device__ __forceinline__ void feature_map(const float (&t)[20], float rl, uint32_t (&o)[20]) {
  float mx = t[0], mn = t[0];
#pragma unroll
  for (int i = 1; i < 20; i++) { mx = fmaxf(mx, t[i]); mn = fminf(mn, t[i]); }
  float bp = -mx * rl, bn = mn * rl;
  float ep[20], en[20];
  float sp = 0.f, sn = 0.f;
#pragma unroll
  for (int i = 0; i < 20; i++) {
    ep[i] = ex2(fmaf(t[i], rl, bp)); sp += ep[i];
    en[i] = ex2(fmaf(t[i], -rl, bn)); sn += en[i];
  }
  float ip = rcp(sp), in = rcp(sn);
#pragma unroll
  for (int i = 0; i < 10; i++) {
    o[i] = pack2(ep[2 * i] * ip, ep[2 * i + 1] * ip);
    o[10 + i] = pack2(en[2 * i] * in, en[2 * i + 1] * in);
  }
}

__device__ __forceinline__ void ld_row20(const __nv_bfloat16* p, uint32_t (&v)[10]) {
#pragma unroll
  for (int i = 0; i < 5; i++) { uint2 t = __ldg(reinterpret_cast<const uint2*>(p) + i); v[2 * i] = t.x; v[2 * i + 1] = t.y; }
}
__device__ __forceinline__ void st_row20(__nv_bfloat16* p, const uint32_t (&v)[10]) {
#pragma unroll
  for (int i = 0; i < 5; i++) reinterpret_cast<uint2*>(p)[i] = make_uint2(v[2 * i], v[2 * i + 1]);
}

__global__ void __launch_bounds__(NTHREADS, 1)
fused_kernel(const __grid_constant__ CUtensorMap tm_x, const __grid_constant__ CUtensorMap tm_act,
             const __grid_constant__ CUtensorMap tm_wts, const __grid_constant__ CUtensorMap tm_u,
             const __grid_constant__ CUtensorMap tm_w1, const __grid_constant__ CUtensorMap tm_w2, const Params prm) {
  extern __shared__ __align__(1024) uint8_t smem[];
  const uint32_t sb = smem_u32(smem);
  const int tid = threadIdx.x, warp = tid >> 5, lane = tid & 31;
  const int c = blockIdx.x;
  const int mt = c >> 3, g = c & 7;
  const bool b1_on = (c & 15) < 15;
  const int dt = (c & 15) % 5, ft = (c >> 4) * 3 + (c & 15) / 5;
  auto FULL = [&](int i) { return sb + SM_BARS + 8 * i; };
  auto EMPTY = [&](int i) { return sb + SM_BARS + 8 * (B_EMPTY + i); };

  if (tid == 0) {
    if (sb & 1023) __trap();
    for (int i = 0; i < B_NRING; i++) { mbar_init(FULL(i), 1); mbar_init(EMPTY(i), 2); }
    mbar_init(FULL(B_MLDONE), 2);
    mbar_init(FULL(B_KVRDY), 1);
    asm volatile("fence.mbarrier_init.release.cluster;" ::: "memory");
  }
  __syncthreads();
  unsigned epoch;
  asm volatile("ld.relaxed.gpu.global.u32 %0, [%1];" : "=r"(epoch) : "l"(&g_epoch) : "memory");
  const unsigned ep1 = epoch + 1;

  if (warp >= 8) {
    asm volatile("setmaxnreg.dec.sync.aligned.u32 40;");
    if (warp == 8) {
      Pos<P1_NA> r1; Pos<P3_NA> r3; Pos<P4_NA> r4; Pos<P5_NB> r5;
      uint32_t mlph = 0;
      for (int layer = 0; layer < 2; layer++) {
        if (lane == 0) {
          if (layer) { mbar_wait(FULL(B_MLDONE), mlph); mlph ^= 1; wait_cnt(C_X + mt, ep1 * 8); fence_async_global(); }
          const CUtensorMap* tm = layer ? &tm_act : &tm_x;
          for (int it = 0; it < 20; it++) {
            int kb = it >= 10 ? it - 10 : it;
            mbar_wait(EMPTY(B_P1A + r1.slot), r1.ph ^ 1);
            uint32_t bar = FULL(B_P1A + r1.slot), dst = sb + P1_A + r1.slot * 16384;
            mbar_expect(bar, 16384);
            tma2d(dst, tm, kb * 64, mt * 128, bar);
            tma2d(dst + 8192, tm, kb * 64, mt * 128 + 64, bar);
            r1.next();
          }
          mbar_wait(FULL(B_MLDONE), mlph); mlph ^= 1;
          wait_cnt(C_O + layer * 16 + mt, ep1 * 8); fence_async_global();
          for (int kb = 0; kb < 10; kb++) {
            mbar_wait(EMPTY(B_P3A + r3.slot), r3.ph ^ 1);
            uint32_t bar = FULL(B_P3A + r3.slot), dst = sb + P3_A + r3.slot * 16384;
            mbar_expect(bar, 16384);
            tma2d(dst, &tm_act, kb * 64, 2048 + mt * 128, bar);
            tma2d(dst + 8192, &tm_act, kb * 64, 2048 + mt * 128 + 64, bar);
            r3.next();
          }
          mbar_wait(FULL(B_MLDONE), mlph); mlph ^= 1;
        }
        __syncwarp();
        if (b1_on) {
          if (lane < 16) wait_cnt(C_H + layer * 16 + lane, ep1 * 8);
          __syncwarp();
          if (lane == 0) {
            if (layer == 1 && c == 0) g_epoch = ep1;
            fence_async_global();
            for (int kb = 0; kb < 32; kb++) {
              mbar_wait(EMPTY(B_P4A + r4.slot), r4.ph ^ 1);
              uint32_t bar = FULL(B_P4A + r4.slot), dst = sb + P4_A + r4.slot * 16384;
              mbar_expect(bar, 16384);
              tma2d(dst, &tm_act, dt * 128, 4096 + kb * 64, bar);
              tma2d(dst + 8192, &tm_act, dt * 128 + 64, 4096 + kb * 64, bar);
              r4.next();
            }
            mbar_wait(FULL(B_MLDONE), mlph); mlph ^= 1;
          }
          __syncwarp();
        }
        {
          int dlo = (80 * g) >> 7, dhi = (80 * g + 79) >> 7;
          if (lane == 0) wait_cnt(C_U + layer * 5 + dlo, ep1 * 24);
          if (lane == 1) wait_cnt(C_U + layer * 5 + dhi, ep1 * 24);
          __syncwarp();
        }
        if (lane == 0) {
          fence_async_global();
          for (int kb = 0; kb < 24; kb++) {
            mbar_wait(EMPTY(B_P5B + r5.slot), r5.ph ^ 1);
            uint32_t bar = FULL(B_P5B + r5.slot), dst = sb + P5_B + r5.slot * 10240;
            mbar_expect(bar, 10240);
            tma2d(dst, &tm_u, kb * 64, g * 80, bar);
            r5.next();
          }
        }
        __syncwarp();
      }
    } else if (warp == 9) {
      if (lane == 0) {
        Pos<P1_NB> r1; Pos<P4_NB> r4; Pos<P5_NA> r5;
        uint32_t mlph = 0;
        for (int layer = 0; layer < 2; layer++) {
          if (layer) { mbar_wait(FULL(B_MLDONE), mlph); mlph ^= 1; }
          else { wait_cnt(C_P0, ep1 * NCTA); fence_async_global(); }
          for (int it = 0; it < 30; it++) {
            int kb = it < 20 ? (it >> 1) : it - 20;
            int row = g * 240 + (it < 20 ? (it & 1) * 80 : 160);
            mbar_wait(EMPTY(B_P1B + r1.slot), r1.ph ^ 1);
            uint32_t bar = FULL(B_P1B + r1.slot);
            mbar_expect(bar, 10240);
            tma2d(sb + P1_B + r1.slot * 10240, &tm_wts, kb * 64, row, bar);
            r1.next();
          }
          mbar_wait(FULL(B_MLDONE), mlph); mlph ^= 1;
          for (int kb = 0; kb < 10; kb++) {
            uint32_t bar = FULL(B_P3B + kb);
            mbar_expect(bar, 10240);
            tma2d(sb + P3_B + kb * 10240, &tm_wts, kb * 64, 1920 + g * 80, bar);
          }
          mbar_wait(FULL(B_MLDONE), mlph); mlph ^= 1;
          if (b1_on) {
            for (int kb = 0; kb < 32; kb++) {
              mbar_wait(EMPTY(B_P4B + r4.slot), r4.ph ^ 1);
              uint32_t bar = FULL(B_P4B + r4.slot);
              mbar_expect(bar, 8192);
              tma2d(sb + P4_B + r4.slot * 8192, &tm_w1, ft * 64, kb * 64, bar);
              r4.next();
            }
            mbar_wait(FULL(B_MLDONE), mlph); mlph ^= 1;
          }
          for (int kb = 0; kb < 24; kb++) {
            mbar_wait(EMPTY(B_P5A + r5.slot), r5.ph ^ 1);
            uint32_t bar = FULL(B_P5A + r5.slot), dst = sb + P5_A + r5.slot * 16384;
            mbar_expect(bar, 16384);
            tma2d(dst, &tm_w2, mt * 128, kb * 64, bar);
            tma2d(dst + 8192, &tm_w2, mt * 128 + 64, kb * 64, bar);
            r5.next();
          }
        }
      }
    } else if (warp == 10) {
      bar_sync(BAR_SIG, 288);
      if (lane == 0) red_rel(&g_cnt[C_P0 * 32]);
      for (int layer = 0; layer < 2; layer++) {
        bar_sync(BAR_SIG, 288);
        if (lane == 0) {
          red_rel(&g_cnt[(C_KV + layer * 8 + g) * 32]);
          wait_cnt(C_KV + layer * 8 + g, ep1 * 16);
          mbar_arrive(FULL(B_KVRDY));
        }
        __syncwarp();
        bar_sync(BAR_SIG, 288);
        if (lane == 0) red_rel(&g_cnt[(C_O + layer * 16 + mt) * 32]);
        __syncwarp();
        bar_sync(BAR_SIG, 288);
        if (lane == 0) red_rel(&g_cnt[(C_H + layer * 16 + mt) * 32]);
        __syncwarp();
        if (b1_on) {
          bar_sync(BAR_SIG2, 288);
          if (lane == 0) red_rel(&g_cnt[(C_U + layer * 5 + dt) * 32]);
          __syncwarp();
        }
        if (layer == 0) {
          bar_sync(BAR_SIG, 288);
          if (lane == 0) red_rel(&g_cnt[(C_X + mt) * 32]);
          __syncwarp();
        }
      }
    } else {
      if (lane < 8) {
        const char* p1 = reinterpret_cast<const char*>(prm.w1) + (size_t)c * 49152 + (lane & 3) * 12288;
        const char* p2 = reinterpret_cast<const char*>(prm.w2) + (size_t)c * 49152 + (lane & 3) * 12288;
        wait_cnt(C_P0, ep1 * NCTA);
        l2_prefetch(lane < 4 ? p1 : p2, 12288);
      }
    }
  } else {
    asm volatile("setmaxnreg.inc.sync.aligned.u32 232;");
    const int wg = warp >> 2, wq = warp & 3, gq = lane >> 2, j = lane & 3;
    const bool elect = (tid & 127) == 0;
    const int lrow = wg * 64 + wq * 16 + gq;
    const int grow = mt * 128 + lrow;
    uint32_t xr[2][10];

    {
      const int type = c >> 5, hh = c & 31;
      const __nv_bfloat16* src = type < 3 ? prm.wqkv + type * 640 + hh * 20 : prm.wo + hh * 20;
      const int ld = type < 3 ? 1920 : 640;
      uint32_t b[10][3];
#pragma unroll
      for (int t = 0; t < 10; t++) {
        const uint32_t* p = reinterpret_cast<const uint32_t*>(src + (size_t)(warp * 80 + t * 8 + gq) * ld);
        b[t][0] = __ldg(p + j); b[t][1] = __ldg(p + j + 4); b[t][2] = j < 2 ? __ldg(p + j + 8) : 0u;
      }
      uint32_t xs[2][10];
      ld_row20(prm.x + (size_t)(c * 16 + warp * 2) * 640 + lane * 20, xs[0]);
      ld_row20(prm.x + (size_t)(c * 16 + warp * 2 + 1) * 640 + lane * 20, xs[1]);
      ld_row20(prm.x + (size_t)grow * 640 + g * 80 + j * 20, xr[0]);
      ld_row20(prm.x + (size_t)(grow + 8) * 640 + g * 80 + j * 20, xr[1]);
      const unsigned short* ph = reinterpret_cast<const unsigned short*>(prm.wphi) + hh * 400;
      auto aval = [&](int f, int d) -> uint32_t {
        if (f >= 20 || d >= 20) return 0u;
        if (type < 2) return (uint32_t)__ldg(ph + d * 20 + f);
        return f == d ? 0x3f80u : 0u;
      };
      auto apair = [&](int f, int d) -> uint32_t { return aval(f, d) | (aval(f, d + 1) << 16); };
      uint32_t a00[4] = {apair(gq, 2 * j), apair(gq + 8, 2 * j), apair(gq, 2 * j + 8), apair(gq + 8, 2 * j + 8)};
      uint32_t a01[4] = {apair(gq, 16 + 2 * j), apair(gq + 8, 16 + 2 * j), 0u, 0u};
      uint32_t a10[4] = {apair(16 + gq, 2 * j), 0u, apair(16 + gq, 2 * j + 8), 0u};
      uint32_t a11[4] = {apair(16 + gq, 16 + 2 * j), 0u, 0u, 0u};
      const int rbase = type < 3 ? (hh >> 2) * 240 + (type == 0 ? 160 : (type == 1 ? 0 : 80)) : 1920 + (hh >> 2) * 80;
      auto drow = [&](int f) { return rbase + 8 * (f >> 1) + 2 * (hh & 3) + (f & 1); };
      uint32_t* d0 = reinterpret_cast<uint32_t*>(g_wts + (size_t)drow(gq) * 640 + warp * 80) + j;
      uint32_t* d1 = reinterpret_cast<uint32_t*>(g_wts + (size_t)drow(gq + 8) * 640 + warp * 80) + j;
      uint32_t* d2 = reinterpret_cast<uint32_t*>(g_wts + (size_t)drow(16 + (gq & 3)) * 640 + warp * 80) + j;
      float cs0 = 0.f, cs1 = 0.f, cs2 = 0.f;
#pragma unroll
      for (int t = 0; t < 10; t++) {
        float c0[4] = {0.f, 0.f, 0.f, 0.f}, c1[4] = {0.f, 0.f, 0.f, 0.f};
        mma16816(c0, a00, b[t][0], b[t][1]);
        mma16816(c0, a01, b[t][2], 0u);
        mma16816(c1, a10, b[t][0], b[t][1]);
        mma16816(c1, a11, b[t][2], 0u);
        uint32_t p0 = pack2(c0[0], c0[1]), p1 = pack2(c0[2], c0[3]), p2 = pack2(c1[0], c1[1]);
        d0[t * 4] = p0; d1[t * 4] = p1;
        if (gq < 4) d2[t * 4] = p2;
        cs0 += lo_f(p0) + hi_f(p0); cs1 += lo_f(p1) + hi_f(p1); cs2 += lo_f(p2) + hi_f(p2);
      }
      cs0 = quad_sum(cs0); cs1 = quad_sum(cs1); cs2 = quad_sum(cs2);
      float* sp = reinterpret_cast<float*>(smem + SM_P0);
      if (j == 0) { sp[warp * 20 + gq] = cs0; sp[warp * 20 + gq + 8] = cs1; if (gq < 4) sp[warp * 20 + 16 + gq] = cs2; }
#pragma unroll
      for (int r = 0; r < 2; r++) {
        float2 st = chunk_stats(xs[r]);
        if (j == 0) g_stats[0][(c * 16 + warp * 2 + r) * 8 + gq] = st;
      }
      if (tid < 210) reinterpret_cast<float2*>(&g_kv[0][0])[c * 210 + tid] = make_float2(0.f, 0.f);
      bar_sync(BAR_CONS, 256);
      if (tid < 20 && type < 3) {
        float s = 0.f;
#pragma unroll
        for (int w = 0; w < 8; w++) s += sp[w * 20 + tid];
        g_colsum[drow(tid)] = s;
      }
      bar_arrive(BAR_SIG, 288);
    }

    Pos<P1_NA> r1a; Pos<P1_NB> r1b; Pos<P3_NA> r3a; Pos<P4_NA> r4a; Pos<P4_NB> r4b; Pos<P5_NA> r5a; Pos<P5_NB> r5b;

    for (int layer = 0; layer < 2; layer++) {
      uint32_t phq[2][20];
      {
        float kvacc[80]; zero(kvacc);
        float mean[2] = {0.f, 0.f}, rl[2] = {0.f, 0.f};
        int pa = 0, pb = 0;
#pragma unroll 1
        for (int kb = 0; kb < 10; kb++) {
          mbar_wait(FULL(B_P1A + r1a.slot), r1a.ph);
          mbar_wait(FULL(B_P1B + r1b.slot), r1b.ph);
          mbar_wait(FULL(B_P1B + r1b.slot + 1), r1b.ph);
          uint64_t da = mkdesc(sb + P1_A + r1a.slot * 16384 + wg * 8192, 16, 1024);
          uint64_t db = mkdesc(sb + P1_B + r1b.slot * 10240, 16, 1024);
          wg_fence();
#pragma unroll
          for (int kk = 0; kk < 4; kk++) wgmma_ss_n160<0, 0>(kvacc, da + kk * 2, db + kk * 2, (kb | kk) != 0);
          wg_commit();
          if (kb == 0) {
#pragma unroll
            for (int r = 0; r < 2; r++) {
              float4 s = __ldcg(reinterpret_cast<const float4*>(&g_stats[layer][(grow + 8 * r) * 8 + 2 * j]));
              float2 mv = combine_stats(s.x, s.y, s.z, s.w);
              mean[r] = mv.x; rl[r] = rsqrtf(mv.y + 1e-5f);
            }
            if (layer == 0 && tid < 240) reinterpret_cast<float*>(smem + SM_CS)[tid] = __ldcg(&g_colsum[g * 240 + tid]);
          } else {
            wg_wait<1>();
            if (elect) { mbar_arrive(EMPTY(B_P1A + pa)); mbar_arrive(EMPTY(B_P1B + pb)); mbar_arrive(EMPTY(B_P1B + pb + 1)); }
          }
          pa = r1a.slot; pb = r1b.slot;
          r1a.next(); r1b.next(); r1b.next();
        }
        wg_wait<0>();
        if (elect) { mbar_arrive(EMPTY(B_P1A + pa)); mbar_arrive(EMPTY(B_P1B + pb)); mbar_arrive(EMPTY(B_P1B + pb + 1)); }
        if (layer == 0) bar_sync(BAR_CONS, 256);

        float qacc[40]; zero(qacc);
        Pos<P1_NA> ra = r1a; Pos<P1_NB> rb = r1b;
        auto q_issue = [&](int kb) {
          mbar_wait(FULL(B_P1A + r1a.slot), r1a.ph);
          mbar_wait(FULL(B_P1B + r1b.slot), r1b.ph);
          uint64_t da = mkdesc(sb + P1_A + r1a.slot * 16384 + wg * 8192, 16, 1024);
          uint64_t db = mkdesc(sb + P1_B + r1b.slot * 10240, 16, 1024);
          wg_fence();
#pragma unroll
          for (int kk = 0; kk < 4; kk++) wgmma_ss_n80<0, 0>(qacc, da + kk * 2, db + kk * 2, (kb | kk) != 0);
          wg_commit();
          r1a.next(); r1b.next();
        };
        auto q_release = [&]() {
          if (elect) { mbar_arrive(EMPTY(B_P1A + ra.slot)); mbar_arrive(EMPTY(B_P1B + rb.slot)); }
          ra.next(); rb.next();
        };
        const uint32_t cs_addr = sb + SM_CS + j * 8;
        const uint32_t stg = sb + P1_STG + (j >> 1) * 32768;
        const int sub = j & 1;
        q_issue(0); q_issue(1);
#pragma unroll
        for (int r = 0; r < 2; r++) {
          float t[20];
#pragma unroll
          for (int i = 0; i < 10; i++) {
            float2 cs = lds64f(cs_addr + i * 32);
            t[2 * i] = fmaf(-mean[r], cs.x, kvacc[i * 4 + 2 * r]);
            t[2 * i + 1] = fmaf(-mean[r], cs.y, kvacc[i * 4 + 2 * r + 1]);
          }
          uint32_t ph[20];
          feature_map(t, rl[r] * LOG2E, ph);
          const int row = lrow + 8 * r;
          const uint32_t rb0 = stg + row * 128, sw = gq;
#pragma unroll
          for (int ch = 0; ch < 5; ch++) {
            int cidx = 5 * sub + ch;
            uint32_t addr = cidx < 8 ? rb0 + ((cidx ^ sw) << 4) : rb0 + 16384 + (((cidx - 2) ^ sw) << 4);
            sts128(addr, ph[4 * ch], ph[4 * ch + 1], ph[4 * ch + 2], ph[4 * ch + 3]);
          }
          uint32_t vv[10];
#pragma unroll
          for (int i = 0; i < 10; i++) {
            float2 cs = lds64f(cs_addr + 320 + i * 32);
            vv[i] = pack2(fmaf(-mean[r], cs.x, kvacc[40 + i * 4 + 2 * r]) * rl[r], fmaf(-mean[r], cs.y, kvacc[40 + i * 4 + 2 * r + 1]) * rl[r]);
          }
          const uint32_t ab = rb0 + 16384;
          sts128(ab + (((3 * sub) ^ sw) << 4), vv[0], vv[1], vv[2], vv[3]);
          sts128(ab + (((3 * sub + 1) ^ sw) << 4), vv[4], vv[5], vv[6], vv[7]);
          sts128(ab + (((3 * sub + 2) ^ sw) << 4), vv[8], vv[9], 0x00003f80u, 0u);
          wg_wait<1>(); q_release(); q_issue(2 + r);
        }
        fence_async_smem();
        bar_sync(BAR_CONS, 256);
        {
          float dacc[40]; zero(dacc);
          const uint32_t pt = sb + P1_STG + wg * 32768;
          uint64_t da = mkdesc(pt + 16384, 16384, 1024);
          uint64_t db = mkdesc(pt, 16384 + 96, 1024);
          wg_fence();
#pragma unroll
          for (int kk = 0; kk < 8; kk++) wgmma_ss_n80<1, 1>(dacc, da + kk * 128, db + kk * 128, kk != 0);
          wg_commit();
          wg_wait<2>(); q_release(); q_issue(4);
          wg_wait<1>(); q_release();
#pragma unroll
          for (int r = 0; r < 2; r++) {
            int rho = wq * 16 + gq + 8 * r;
            int sr = rho >= 24, dd = rho - 24 * sr;
            if (dd <= 20) {
              float* dst = &g_kv[layer][(4 * g + 2 * wg + sr) * 840 + dd * 40 + 2 * j];
#pragma unroll
              for (int ii = 0; ii < 5; ii++) {
                float v0 = sr ? dacc[(5 + ii) * 4 + 2 * r] : dacc[ii * 4 + 2 * r];
                float v1 = sr ? dacc[(5 + ii) * 4 + 2 * r + 1] : dacc[ii * 4 + 2 * r + 1];
                red_add2(dst + ii * 8, v0, v1);
              }
            }
          }
          bar_arrive(BAR_SIG, 288);
        }
#pragma unroll 1
        for (int kb = 5; kb < 10; kb++) { q_issue(kb); wg_wait<1>(); q_release(); }
        wg_wait<0>(); q_release();
        if (elect) mbar_arrive(FULL(B_MLDONE));
#pragma unroll
        for (int r = 0; r < 2; r++) {
          float t[20];
#pragma unroll
          for (int i = 0; i < 10; i++) {
            float2 cs = lds64f(cs_addr + 640 + i * 32);
            t[2 * i] = fmaf(-mean[r], cs.x, qacc[i * 4 + 2 * r]);
            t[2 * i + 1] = fmaf(-mean[r], cs.y, qacc[i * 4 + 2 * r + 1]);
          }
          feature_map(t, rl[r] * LOG2E, phq[r]);
        }
      }
      {
        mbar_wait(FULL(B_KVRDY), layer);
        const float* kvp = &g_kv[layer][4 * g * 840];
        float2 kvv[7] = {};
#pragma unroll
        for (int it = 0; it < 7; it++) {
          int idx = tid + 256 * it;
          if (idx < 1680) {
            int nn = idx / 20, ch = idx - nn * 20;
            int hj = nn < 80 ? (nn & 7) >> 1 : nn - 80;
            int dim = nn < 80 ? 2 * (nn >> 3) + (nn & 1) : 20;
            kvv[it] = __ldcg(reinterpret_cast<const float2*>(kvp + hj * 840 + dim * 40 + 2 * ch));
          }
        }
#pragma unroll
        for (int it = 0; it < 7; it++) {
          int idx = tid + 256 * it;
          if (idx < 1680) {
            int nn = idx / 20, ch = idx - nn * 20;
            int hj = nn < 80 ? (nn & 7) >> 1 : nn - 80;
            int n = nn < 80 ? nn : 80 + 2 * hj;
            uint32_t v = pack2(kvv[it].x, kvv[it].y);
            uint32_t addr = sb + P1_STG + (ch >> 3) * 11264 + n * 128 + (((ch & 7) ^ (n & 7)) << 4);
            sts128(addr, hj == 0 ? v : 0u, hj == 1 ? v : 0u, hj == 2 ? v : 0u, hj == 3 ? v : 0u);
          }
        }
        fence_async_smem();
        bar_sync(BAR_CONS, 256);
        float oacc[44]; zero(oacc);
        wg_fence();
#pragma unroll
        for (int t = 0; t < 10; t++) {
          uint32_t a[4] = {phq[0][2 * t], phq[1][2 * t], phq[0][2 * t + 1], phq[1][2 * t + 1]};
          uint64_t db = mkdesc(sb + P1_STG + (t >> 2) * 11264 + (t & 3) * 32, 16, 1024);
          wgmma_rs_n88<0>(oacc, a, db, t != 0);
        }
        wg_commit();
        wg_wait<0>();
#pragma unroll
        for (int r = 0; r < 2; r++) {
          float inv = rcp(oacc[40 + 2 * r] + 1e-6f);
          uint32_t ov[10];
#pragma unroll
          for (int i = 0; i < 10; i++) ov[i] = pack2(oacc[i * 4 + 2 * r] * inv, oacc[i * 4 + 2 * r + 1] * inv);
          st_row20(g_act + (size_t)(2048 + grow + 8 * r) * 640 + g * 80 + j * 20, ov);
        }
        bar_arrive(BAR_SIG, 288);
      }
      {
        float acc[40]; zero(acc);
        int pa = 0;
#pragma unroll 1
        for (int kb = 0; kb < 10; kb++) {
          mbar_wait(FULL(B_P3A + r3a.slot), r3a.ph);
          mbar_wait(FULL(B_P3B + kb), layer);
          uint64_t da = mkdesc(sb + P3_A + r3a.slot * 16384 + wg * 8192, 16, 1024);
          uint64_t db = mkdesc(sb + P3_B + kb * 10240, 16, 1024);
          wg_fence();
#pragma unroll
          for (int kk = 0; kk < 4; kk++) wgmma_ss_n80<0, 0>(acc, da + kk * 2, db + kk * 2, (kb | kk) != 0);
          wg_commit();
          if (kb) { wg_wait<1>(); if (elect) mbar_arrive(EMPTY(B_P3A + pa)); }
          pa = r3a.slot; r3a.next();
        }
        wg_wait<0>();
        if (elect) { mbar_arrive(EMPTY(B_P3A + pa)); mbar_arrive(FULL(B_MLDONE)); }
        const unsigned tag = ep1;
#pragma unroll
        for (int r = 0; r < 2; r++) {
#pragma unroll
          for (int i = 0; i < 10; i++)
            xr[r][i] = pack2(lo_f(xr[r][i]) + acc[i * 4 + 2 * r], hi_f(xr[r][i]) + acc[i * 4 + 2 * r + 1]);
          float2 st = chunk_stats(xr[r]);
          if (j == r) st_vol4(&g_ll[layer][(grow + 8 * r) * 8 + g], make_uint4(__float_as_uint(st.x), tag, __float_as_uint(st.y), tag));
        }
        uint4 l[2][2];
        {
          int n = 0;
          bool ok;
          do {
#pragma unroll
            for (int r = 0; r < 2; r++) {
              l[r][0] = ld_vol4(&g_ll[layer][(grow + 8 * r) * 8 + 2 * j]);
              l[r][1] = ld_vol4(&g_ll[layer][(grow + 8 * r) * 8 + 2 * j + 1]);
            }
            ok = l[0][0].y == tag && l[0][0].w == tag && l[0][1].y == tag && l[0][1].w == tag &&
                 l[1][0].y == tag && l[1][0].w == tag && l[1][1].y == tag && l[1][1].w == tag;
            if (++n > (1 << 21)) __trap();
          } while (!ok);
        }
        __syncwarp();
#pragma unroll
        for (int r = 0; r < 2; r++) {
          float2 mv = combine_stats(__uint_as_float(l[r][0].x), __uint_as_float(l[r][0].z), __uint_as_float(l[r][1].x), __uint_as_float(l[r][1].z));
          float ve = mv.y + 1e-5f;
          float rr = rsqrtf(ve) * rsqrtf(mv.y / ve + 1e-5f);
          float nb = -mv.x * rr;
          uint32_t hv[10];
#pragma unroll
          for (int i = 0; i < 10; i++) hv[i] = pack2(fmaf(lo_f(xr[r][i]), rr, nb), fmaf(hi_f(xr[r][i]), rr, nb));
          st_row20(g_act + (size_t)(4096 + grow + 8 * r) * 640 + g * 80 + j * 20, hv);
        }
        bar_arrive(BAR_SIG, 288);
      }
      if (b1_on) {
        float acc[32]; zero(acc);
        uint32_t bias[8];
#pragma unroll
        for (int i = 0; i < 8; i++) bias[i] = __ldg(reinterpret_cast<const uint32_t*>(prm.b1 + ft * 64 + i * 8) + j);
        int pa = 0, pb = 0;
#pragma unroll 1
        for (int kb = 0; kb < 32; kb++) {
          mbar_wait(FULL(B_P4A + r4a.slot), r4a.ph);
          mbar_wait(FULL(B_P4B + r4b.slot), r4b.ph);
          uint64_t da = mkdesc(sb + P4_A + r4a.slot * 16384 + wg * 8192, 8192, 1024);
          uint64_t db = mkdesc(sb + P4_B + r4b.slot * 8192, 8192, 1024);
          wg_fence();
#pragma unroll
          for (int kk = 0; kk < 4; kk++) wgmma_ss_n64<1, 1>(acc, da + kk * 128, db + kk * 128, (kb | kk) != 0);
          wg_commit();
          if (kb) { wg_wait<1>(); if (elect) { mbar_arrive(EMPTY(B_P4A + pa)); mbar_arrive(EMPTY(B_P4B + pb)); } }
          pa = r4a.slot; pb = r4b.slot; r4a.next(); r4b.next();
        }
        wg_wait<0>();
        if (elect) { mbar_arrive(EMPTY(B_P4A + pa)); mbar_arrive(EMPTY(B_P4B + pb)); mbar_arrive(FULL(B_MLDONE)); }
#pragma unroll
        for (int r = 0; r < 2; r++) {
          int d = dt * 128 + lrow + 8 * r;
          int nt = d / 80, w = d - nt * 80, jj = w / 20, rem = w - jj * 20;
          int prow = nt * 80 + 8 * (rem >> 1) + 2 * jj + (rem & 1);
          uint32_t* dst = reinterpret_cast<uint32_t*>(g_u + (size_t)prow * 1536 + ft * 64) + j;
#pragma unroll
          for (int i = 0; i < 8; i++) {
            float v0 = acc[i * 4 + 2 * r] + lo_f(bias[i]), v1 = acc[i * 4 + 2 * r + 1] + hi_f(bias[i]);
            float t0 = tanh_a(v0 * fmaf(v0 * v0, 0.0356774081f, 0.7978845608f));
            float t1 = tanh_a(v1 * fmaf(v1 * v1, 0.0356774081f, 0.7978845608f));
            float h0 = 0.5f * v0, h1 = 0.5f * v1;
            dst[i * 4] = pack2(fmaf(h0, t0, h0), fmaf(h1, t1, h1));
          }
        }
        bar_arrive(BAR_SIG2, 288);
      }
      {
        float acc[40]; zero(acc);
        float b2v[2];
        b2v[0] = __bfloat162float(prm.b2[grow]); b2v[1] = __bfloat162float(prm.b2[grow + 8]);
        int pa = 0, pb = 0;
#pragma unroll 1
        for (int kb = 0; kb < 24; kb++) {
          mbar_wait(FULL(B_P5A + r5a.slot), r5a.ph);
          mbar_wait(FULL(B_P5B + r5b.slot), r5b.ph);
          uint64_t da = mkdesc(sb + P5_A + r5a.slot * 16384 + wg * 8192, 8192, 1024);
          uint64_t db = mkdesc(sb + P5_B + r5b.slot * 10240, 16, 1024);
          wg_fence();
#pragma unroll
          for (int kk = 0; kk < 4; kk++) wgmma_ss_n80<1, 0>(acc, da + kk * 128, db + kk * 2, (kb | kk) != 0);
          wg_commit();
          if (kb) { wg_wait<1>(); if (elect) { mbar_arrive(EMPTY(B_P5A + pa)); mbar_arrive(EMPTY(B_P5B + pb)); } }
          pa = r5a.slot; pb = r5b.slot; r5a.next(); r5b.next();
        }
        wg_wait<0>();
        if (elect) { mbar_arrive(EMPTY(B_P5A + pa)); mbar_arrive(EMPTY(B_P5B + pb)); mbar_arrive(FULL(B_MLDONE)); }
        __nv_bfloat16* dst = layer ? prm.out : g_act;
#pragma unroll
        for (int r = 0; r < 2; r++) {
#pragma unroll
          for (int i = 0; i < 10; i++)
            xr[r][i] = pack2(lo_f(xr[r][i]) + (acc[i * 4 + 2 * r] + b2v[r]), hi_f(xr[r][i]) + (acc[i * 4 + 2 * r + 1] + b2v[r]));
          st_row20(dst + (size_t)(grow + 8 * r) * 640 + g * 80 + j * 20, xr[r]);
          if (layer == 0) {
            float2 st = chunk_stats(xr[r]);
            if (j == r) g_stats[1][(grow + 8 * r) * 8 + g] = st;
          }
        }
        if (layer == 0) bar_arrive(BAR_SIG, 288);
      }
    }
  }
}

typedef CUresult (*EncodeFn)(CUtensorMap*, CUtensorMapDataType, cuuint32_t, void*, const cuuint64_t*, const cuuint64_t*,
                             const cuuint32_t*, const cuuint32_t*, CUtensorMapInterleave, CUtensorMapSwizzle,
                             CUtensorMapL2promotion, CUtensorMapFloatOOBfill);

void make_map(EncodeFn fn, CUtensorMap* m, const void* base, uint64_t cols, uint64_t rows, uint32_t box_rows) {
  cuuint64_t dims[2] = {cols, rows};
  cuuint64_t strides[1] = {cols * 2};
  cuuint32_t box[2] = {64, box_rows};
  cuuint32_t es[2] = {1, 1};
  fn(m, CU_TENSOR_MAP_DATA_TYPE_BFLOAT16, 2, const_cast<void*>(base), dims, strides, box, es, CU_TENSOR_MAP_INTERLEAVE_NONE,
     CU_TENSOR_MAP_SWIZZLE_128B, CU_TENSOR_MAP_L2_PROMOTION_L2_256B, CU_TENSOR_MAP_FLOAT_OOB_FILL_NONE);
}

}

extern "C" void kernel_launch(void* const* d_in, const int* in_sizes, int n_in, void* d_out, int out_size) {
  static bool init = false;
  static CUtensorMap tm_x, tm_act, tm_wts, tm_u, tm_w1, tm_w2;
  static const void* cached[3] = {nullptr, nullptr, nullptr};
  if (!init || cached[0] != d_in[0] || cached[1] != d_in[5] || cached[2] != d_in[7]) {
    void* fnp = nullptr;
    cudaDriverEntryPointQueryResult qr;
    cudaGetDriverEntryPoint("cuTensorMapEncodeTiled", &fnp, cudaEnableDefault, &qr);
    EncodeFn fn = (EncodeFn)fnp;
    void *p_act, *p_wts, *p_u;
    cudaGetSymbolAddress(&p_act, g_act);
    cudaGetSymbolAddress(&p_wts, g_wts);
    cudaGetSymbolAddress(&p_u, g_u);
    make_map(fn, &tm_x, d_in[0], 640, 2048, 64);
    make_map(fn, &tm_act, p_act, 640, 3 * 2048, 64);
    make_map(fn, &tm_wts, p_wts, 640, 2560, 80);
    make_map(fn, &tm_u, p_u, 1536, 640, 80);
    make_map(fn, &tm_w1, d_in[5], 1536, 2048, 64);
    make_map(fn, &tm_w2, d_in[7], 2048, 1536, 64);
    cudaFuncSetAttribute(fused_kernel, cudaFuncAttributeMaxDynamicSharedMemorySize, SM_TOTAL);
    cached[0] = d_in[0]; cached[1] = d_in[5]; cached[2] = d_in[7];
    init = true;
  }
  Params p;
  p.x = (const __nv_bfloat16*)d_in[0];
  p.wqkv = (const __nv_bfloat16*)d_in[1];
  p.wphi = (const __nv_bfloat16*)d_in[2];
  p.wo = (const __nv_bfloat16*)d_in[3];
  p.w1 = (const __nv_bfloat16*)d_in[5];
  p.b1 = (const __nv_bfloat16*)d_in[6];
  p.w2 = (const __nv_bfloat16*)d_in[7];
  p.b2 = (const __nv_bfloat16*)d_in[8];
  p.out = (__nv_bfloat16*)d_out;
  fused_kernel<<<NCTA, NTHREADS, SM_TOTAL>>>(tm_x, tm_act, tm_wts, tm_u, tm_w1, tm_w2, p);
}
```

```cpp
#include <cuda_runtime.h>
#include <cuda_bf16.h>
#include <cuda.h>
#include <stdint.h>

namespace {

constexpr int NCTA = 128;
constexpr int NTHREADS = 384;

constexpr int R_WQKV = 0, R_WO = 1920, R_X2 = 2560, R_O = R_X2 + 2048, R_H = R_O + 2048, R_END = R_H + 2048;
__device__ __align__(1024) __nv_bfloat16 g_buf[R_END * 640];
__device__ __align__(1024) __nv_bfloat16 g_u[640 * 1536];
__device__ __align__(16) float g_colsum[8 * 1920];
__device__ __align__(16) float2 g_stats[2][2048 * 8];
__device__ __align__(16) float g_kv[2][32 * 840];
__device__ __align__(16) uint4 g_ll[2][2048 * 8];
constexpr int C_P0 = 0, C_KV = 1, C_O = C_KV + 16, C_H = C_O + 32, C_U = C_H + 32, C_X = C_U + 10, C_NUM = C_X + 16;
__device__ __align__(128) unsigned g_cnt[C_NUM * 32];
__device__ unsigned g_epoch;

#define TS(i) do {} while (0)

constexpr int KB = 1024;
constexpr int SM_MISC = 224 * KB;
constexpr int SM_BARS = SM_MISC;
constexpr int SM_CS = SM_MISC + 1280;
constexpr int SM_ABORT = SM_CS + 960;
constexpr int SM_ST = 204 * KB;
constexpr int SM_TOTAL = 227 * KB;
constexpr int P1_NA = 5, P1_NB = 8, P1_A = 0, P1_B = 80 * KB, P1_STG = 160 * KB;
constexpr int P3_NA = 6, P3_NB = 10, P3_B = 0, P3_A = 100 * KB;
constexpr int P4_NA = 6, P4_NB = 13, P4_B = 0, P4_A = 104 * KB;
constexpr int P5_NA = 8, P5_NB = 7, P5_A = 0, P5_B = 128 * KB;
constexpr int B_P1A = 0, B_P1B = B_P1A + P1_NA, B_P3A = B_P1B + P1_NB, B_P3B = B_P3A + P3_NA, B_P4A = B_P3B + P3_NB,
              B_P4B = B_P4A + P4_NA, B_P5A = B_P4B + P4_NB, B_P5B = B_P5A + P5_NA, B_NRING = B_P5B + P5_NB;
constexpr int B_EMPTY = 68;
constexpr int B_MLDONE = 136, B_KVRDY = 137;

__device__ __forceinline__ uint32_t smem_u32(const void* p) { return (uint32_t)__cvta_generic_to_shared(p); }
__device__ __forceinline__ void mbar_init(uint32_t a, int c) { asm volatile("mbarrier.init.shared::cta.b64 [%0], %1;" ::"r"(a), "r"(c)); }
__device__ __forceinline__ void mbar_expect(uint32_t a, int bytes) {
  asm volatile("mbarrier.arrive.expect_tx.shared::cta.b64 _, [%0], %1;" ::"r"(a), "r"(bytes) : "memory");
}
__device__ __forceinline__ void mbar_arrive(uint32_t a) { asm volatile("mbarrier.arrive.shared::cta.b64 _, [%0];" ::"r"(a) : "memory"); }
__device__ __forceinline__ bool mbar_try(uint32_t a, uint32_t ph) {
  uint32_t ok;
  asm volatile("{\n.reg .pred p;\nmbarrier.try_wait.parity.shared::cta.b64 p, [%1], %2;\nselp.u32 %0, 1, 0, p;\n}" : "=r"(ok) : "r"(a), "r"(ph) : "memory");
  return ok;
}
__device__ __forceinline__ bool timed_out(int n) {
  if (n & 255) return false;
  extern __shared__ __align__(1024) uint8_t smem_raw[];
  volatile int* ab = reinterpret_cast<volatile int*>(smem_raw + SM_ABORT);
  if (n > (1 << 21)) *ab = 1;
  return *ab != 0;
}
__device__ __forceinline__ void mbar_wait(uint32_t a, uint32_t ph) {
  if (mbar_try(a, ph)) return;
  int n = 0;
  while (!mbar_try(a, ph)) { if (timed_out(++n)) break; }
}
__device__ __forceinline__ void tma2d(uint32_t dst, const CUtensorMap* m, int c0, int c1, uint32_t bar) {
  asm volatile("cp.async.bulk.tensor.2d.shared::cluster.global.mbarrier::complete_tx::bytes [%0], [%1, {%3, %4}], [%2];"
               ::"r"(dst), "l"(m), "r"(bar), "r"(c0), "r"(c1) : "memory");
}
__device__ __forceinline__ void tma5d(uint32_t dst, const CUtensorMap* m, int c0, int c4, uint32_t bar) {
  asm volatile("cp.async.bulk.tensor.5d.shared::cluster.global.mbarrier::complete_tx::bytes [%0], [%1, {%3, %5, %5, %5, %4}], [%2];"
               ::"r"(dst), "l"(m), "r"(bar), "r"(c0), "r"(c4), "r"(0) : "memory");
}
__device__ __forceinline__ void tma_store2d(const CUtensorMap* m, int c0, int c1, uint32_t src) {
  asm volatile("cp.async.bulk.tensor.2d.global.shared::cta.bulk_group [%0, {%2, %3}], [%1];" ::"l"(m), "r"(src), "r"(c0), "r"(c1) : "memory");
}
__device__ __forceinline__ void bulk_commit_wait() {
  asm volatile("cp.async.bulk.commit_group;\ncp.async.bulk.wait_group 0;" ::: "memory");
}
__device__ __forceinline__ void sts64(uint32_t a, uint32_t x, uint32_t y) {
  asm volatile("st.shared.v2.b32 [%0], {%1, %2};" ::"r"(a), "r"(x), "r"(y) : "memory");
}
__device__ __forceinline__ void sts32(uint32_t a, uint32_t x) { asm volatile("st.shared.b32 [%0], %1;" ::"r"(a), "r"(x) : "memory"); }
__device__ __forceinline__ void l2_prefetch(const void* p, int bytes) {
  asm volatile("cp.async.bulk.prefetch.L2.global [%0], %1;" ::"l"(p), "r"(bytes) : "memory");
}
__device__ __forceinline__ unsigned ld_acq(const unsigned* p) {
  unsigned v; asm volatile("ld.acquire.gpu.global.u32 %0, [%1];" : "=r"(v) : "l"(p) : "memory"); return v;
}
__device__ __forceinline__ void red_rel(unsigned* p) { asm volatile("red.release.gpu.global.add.u32 [%0], 1;" ::"l"(p) : "memory"); }
__device__ __forceinline__ void wait_cnt(int idx, unsigned target) {
  const unsigned* p = &g_cnt[idx * 32];
  int n = 0;
  while ((int)(ld_acq(p) - target) < 0) { if (timed_out(++n)) break; }
}
__device__ __forceinline__ void fence_async_global() { asm volatile("fence.proxy.async.global;" ::: "memory"); }
__device__ __forceinline__ void fence_async_smem() { asm volatile("fence.proxy.async.shared::cta;" ::: "memory"); }
__device__ __forceinline__ void bar_sync(int id, int n) { asm volatile("bar.sync %0, %1;" ::"r"(id), "r"(n) : "memory"); }
__device__ __forceinline__ void bar_arrive(int id, int n) { asm volatile("bar.arrive %0, %1;" ::"r"(id), "r"(n) : "memory"); }
__device__ __forceinline__ void wg_fence() { asm volatile("wgmma.fence.sync.aligned;" ::: "memory"); }
__device__ __forceinline__ void wg_commit() { asm volatile("wgmma.commit_group.sync.aligned;" ::: "memory"); }
template <int N> __device__ __forceinline__ void wg_wait() { asm volatile("wgmma.wait_group.sync.aligned %0;" ::"n"(N) : "memory"); }
__device__ __forceinline__ uint64_t mkdesc(uint32_t addr, uint32_t lbo, uint32_t sbo) {
  return (uint64_t)((addr & 0x3FFFF) >> 4) | ((uint64_t)(lbo >> 4) << 16) | ((uint64_t)(sbo >> 4) << 32) | (1ull << 62);
}
__device__ __forceinline__ uint32_t pack2(float lo, float hi) {
  uint32_t r; asm("cvt.rn.bf16x2.f32 %0, %1, %2;" : "=r"(r) : "f"(hi), "f"(lo)); return r;
}
__device__ __forceinline__ float lo_f(uint32_t v) { return __uint_as_float(v << 16); }
__device__ __forceinline__ float hi_f(uint32_t v) { return __uint_as_float(v & 0xffff0000u); }
__device__ __forceinline__ float ex2(float x) { float r; asm("ex2.approx.ftz.f32 %0, %1;" : "=f"(r) : "f"(x)); return r; }
__device__ __forceinline__ float rcp(float x) { float r; asm("rcp.approx.ftz.f32 %0, %1;" : "=f"(r) : "f"(x)); return r; }
__device__ __forceinline__ float tanh_a(float x) { float r; asm("tanh.approx.f32 %0, %1;" : "=f"(r) : "f"(x)); return r; }
__device__ __forceinline__ void sts128(uint32_t a, uint32_t x, uint32_t y, uint32_t z, uint32_t w) {
  asm volatile("st.shared.v4.b32 [%0], {%1, %2, %3, %4};" ::"r"(a), "r"(x), "r"(y), "r"(z), "r"(w) : "memory");
}
__device__ __forceinline__ float2 lds64f(uint32_t a) {
  float2 v; asm volatile("ld.shared.v2.f32 {%0, %1}, [%2];" : "=f"(v.x), "=f"(v.y) : "r"(a)); return v;
}
__device__ __forceinline__ void red_add2(float* p, float a, float b) {
  asm volatile("red.relaxed.gpu.global.add.v2.f32 [%0], {%1, %2};" ::"l"(p), "f"(a), "f"(b) : "memory");
}
__device__ __forceinline__ uint4 ld_vol4(const uint4* p) {
  uint4 v; asm volatile("ld.relaxed.gpu.global.v4.u32 {%0, %1, %2, %3}, [%4];" : "=r"(v.x), "=r"(v.y), "=r"(v.z), "=r"(v.w) : "l"(p) : "memory"); return v;
}
__device__ __forceinline__ void st_vol4(uint4* p, uint4 v) {
  asm volatile("st.relaxed.gpu.global.v4.u32 [%0], {%1, %2, %3, %4};" ::"l"(p), "r"(v.x), "r"(v.y), "r"(v.z), "r"(v.w) : "memory");
}
__device__ __forceinline__ void mma16816(float (&c)[4], const uint32_t (&a)[4], uint32_t b0, uint32_t b1) {
  asm volatile("mma.sync.aligned.m16n8k16.row.col.f32.bf16.bf16.f32 {%0,%1,%2,%3}, {%4,%5,%6,%7}, {%8,%9}, {%0,%1,%2,%3};"
               : "+f"(c[0]), "+f"(c[1]), "+f"(c[2]), "+f"(c[3]) : "r"(a[0]), "r"(a[1]), "r"(a[2]), "r"(a[3]), "r"(b0), "r"(b1));
}
__device__ __forceinline__ float quad_sum(float v) {
  v += __shfl_xor_sync(0xffffffffu, v, 1);
  v += __shfl_xor_sync(0xffffffffu, v, 2);
  return v;
}
template<int TA, int TB> __device__ __forceinline__ void wgmma_ss_n64(float (&d)[32], uint64_t da, uint64_t db, int sd) {
  asm volatile("{\n.reg .pred p;\nsetp.ne.b32 p, %34, 0;\n"
    "wgmma.mma_async.sync.aligned.m64n64k16.f32.bf16.bf16 "
    "{%0, %1, %2, %3, %4, %5, %6, %7, %8, %9, %10, %11, %12, %13, %14, %15, %16, %17, %18, %19, %20, %21, %22, %23, %24, %25, %26, %27, %28, %29, %30, %31}, %32, %33, p, 1, 1, %35, %36;\n}\n"
    : "+f"(d[0]), "+f"(d[1]), "+f"(d[2]), "+f"(d[3]), "+f"(d[4]), "+f"(d[5]), "+f"(d[6]), "+f"(d[7]), "+f"(d[8]), "+f"(d[9]), "+f"(d[10]), "+f"(d[11]), "+f"(d[12]), "+f"(d[13]), "+f"(d[14]), "+f"(d[15]), "+f"(d[16]), "+f"(d[17]), "+f"(d[18]), "+f"(d[19]), "+f"(d[20]), "+f"(d[21]), "+f"(d[22]), "+f"(d[23]), "+f"(d[24]), "+f"(d[25]), "+f"(d[26]), "+f"(d[27]), "+f"(d[28]), "+f"(d[29]), "+f"(d[30]), "+f"(d[31])
    : "l"(da), "l"(db), "r"(sd), "n"(TA), "n"(TB));
}
template<int TA, int TB> __device__ __forceinline__ void wgmma_ss_n80(float (&d)[40], uint64_t da, uint64_t db, int sd) {
  asm volatile("{\n.reg .pred p;\nsetp.ne.b32 p, %42, 0;\n"
    "wgmma.mma_async.sync.aligned.m64n80k16.f32.bf16.bf16 "
    "{%0, %1, %2, %3, %4, %5, %6, %7, %8, %9, %10, %11, %12, %13, %14, %15, %16, %17, %18, %19, %20, %21, %22, %23, %24, %25, %26, %27, %28, %29, %30, %31, %32, %33, %34, %35, %36, %37, %38, %39}, %40, %41, p, 1, 1, %43, %44;\n}\n"
    : "+f"(d[0]), "+f"(d[1]), "+f"(d[2]), "+f"(d[3]), "+f"(d[4]), "+f"(d[5]), "+f"(d[6]), "+f"(d[7]), "+f"(d[8]), "+f"(d[9]), "+f"(d[10]), "+f"(d[11]), "+f"(d[12]), "+f"(d[13]), "+f"(d[14]), "+f"(d[15]), "+f"(d[16]), "+f"(d[17]), "+f"(d[18]), "+f"(d[19]), "+f"(d[20]), "+f"(d[21]), "+f"(d[22]), "+f"(d[23]), "+f"(d[24]), "+f"(d[25]), "+f"(d[26]), "+f"(d[27]), "+f"(d[28]), "+f"(d[29]), "+f"(d[30]), "+f"(d[31]), "+f"(d[32]), "+f"(d[33]), "+f"(d[34]), "+f"(d[35]), "+f"(d[36]), "+f"(d[37]), "+f"(d[38]), "+f"(d[39])
    : "l"(da), "l"(db), "r"(sd), "n"(TA), "n"(TB));
}
template<int TA, int TB> __device__ __forceinline__ void wgmma_ss_n160(float (&d)[80], uint64_t da, uint64_t db, int sd) {
  asm volatile("{\n.reg .pred p;\nsetp.ne.b32 p, %82, 0;\n"
    "wgmma.mma_async.sync.aligned.m64n160k16.f32.bf16.bf16 "
    "{%0, %1, %2, %3, %4, %5, %6, %7, %8, %9, %10, %11, %12, %13, %14, %15, %16, %17, %18, %19, %20, %21, %22, %23, %24, %25, %26, %27, %28, %29, %30, %31, %32, %33, %34, %35, %36, %37, %38, %39, %40, %41, %42, %43, %44, %45, %46, %47, %48, %49, %50, %51, %52, %53, %54, %55, %56, %57, %58, %59, %60, %61, %62, %63, %64, %65, %66, %67, %68, %69, %70, %71, %72, %73, %74, %75, %76, %77, %78, %79}, %80, %81, p, 1, 1, %83, %84;\n}\n"
    : "+f"(d[0]), "+f"(d[1]), "+f"(d[2]), "+f"(d[3]), "+f"(d[4]), "+f"(d[5]), "+f"(d[6]), "+f"(d[7]), "+f"(d[8]), "+f"(d[9]), "+f"(d[10]), "+f"(d[11]), "+f"(d[12]), "+f"(d[13]), "+f"(d[14]), "+f"(d[15]), "+f"(d[16]), "+f"(d[17]), "+f"(d[18]), "+f"(d[19]), "+f"(d[20]), "+f"(d[21]), "+f"(d[22]), "+f"(d[23]), "+f"(d[24]), "+f"(d[25]), "+f"(d[26]), "+f"(d[27]), "+f"(d[28]), "+f"(d[29]), "+f"(d[30]), "+f"(d[31]), "+f"(d[32]), "+f"(d[33]), "+f"(d[34]), "+f"(d[35]), "+f"(d[36]), "+f"(d[37]), "+f"(d[38]), "+f"(d[39]), "+f"(d[40]), "+f"(d[41]), "+f"(d[42]), "+f"(d[43]), "+f"(d[44]), "+f"(d[45]), "+f"(d[46]), "+f"(d[47]), "+f"(d[48]), "+f"(d[49]), "+f"(d[50]), "+f"(d[51]), "+f"(d[52]), "+f"(d[53]), "+f"(d[54]), "+f"(d[55]), "+f"(d[56]), "+f"(d[57]), "+f"(d[58]), "+f"(d[59]), "+f"(d[60]), "+f"(d[61]), "+f"(d[62]), "+f"(d[63]), "+f"(d[64]), "+f"(d[65]), "+f"(d[66]), "+f"(d[67]), "+f"(d[68]), "+f"(d[69]), "+f"(d[70]), "+f"(d[71]), "+f"(d[72]), "+f"(d[73]), "+f"(d[74]), "+f"(d[75]), "+f"(d[76]), "+f"(d[77]), "+f"(d[78]), "+f"(d[79])
    : "l"(da), "l"(db), "r"(sd), "n"(TA), "n"(TB));
}
template<int TB> __device__ __forceinline__ void wgmma_rs_n88(float (&d)[44], const uint32_t (&a)[4], uint64_t db, int sd) {
  asm volatile("{\n.reg .pred p;\nsetp.ne.b32 p, %49, 0;\n"
    "wgmma.mma_async.sync.aligned.m64n88k16.f32.bf16.bf16 "
    "{%0, %1, %2, %3, %4, %5, %6, %7, %8, %9, %10, %11, %12, %13, %14, %15, %16, %17, %18, %19, %20, %21, %22, %23, %24, %25, %26, %27, %28, %29, %30, %31, %32, %33, %34, %35, %36, %37, %38, %39, %40, %41, %42, %43}, {%44, %45, %46, %47}, %48, p, 1, 1, %50;\n}\n"
    : "+f"(d[0]), "+f"(d[1]), "+f"(d[2]), "+f"(d[3]), "+f"(d[4]), "+f"(d[5]), "+f"(d[6]), "+f"(d[7]), "+f"(d[8]), "+f"(d[9]), "+f"(d[10]), "+f"(d[11]), "+f"(d[12]), "+f"(d[13]), "+f"(d[14]), "+f"(d[15]), "+f"(d[16]), "+f"(d[17]), "+f"(d[18]), "+f"(d[19]), "+f"(d[20]), "+f"(d[21]), "+f"(d[22]), "+f"(d[23]), "+f"(d[24]), "+f"(d[25]), "+f"(d[26]), "+f"(d[27]), "+f"(d[28]), "+f"(d[29]), "+f"(d[30]), "+f"(d[31]), "+f"(d[32]), "+f"(d[33]), "+f"(d[34]), "+f"(d[35]), "+f"(d[36]), "+f"(d[37]), "+f"(d[38]), "+f"(d[39]), "+f"(d[40]), "+f"(d[41]), "+f"(d[42]), "+f"(d[43])
    : "r"(a[0]), "r"(a[1]), "r"(a[2]), "r"(a[3]), "l"(db), "r"(sd), "n"(TB));
}

template <int N> struct Pos {
  int slot = 0; uint32_t ph = 0;
  __device__ __forceinline__ void next() { if (++slot == N) { slot = 0; ph ^= 1; } }
};

template <int N> __device__ __forceinline__ void zero(float (&a)[N]) {
#pragma unroll
  for (int i = 0; i < N; i++) a[i] = 0.f;
}

struct Params {
  const __nv_bfloat16 *x, *wqkv, *wphi, *wo, *w1, *b1, *w2, *b2;
  __nv_bfloat16* out;
};

constexpr int BAR_CONS = 1, BAR_SIG = 2, BAR_SIG2 = 3;
constexpr float LOG2E = 1.4426950408889634f;

__device__ __forceinline__ float2 chunk_stats(const uint32_t (&v)[10]) {
  float s = 0.f;
#pragma unroll
  for (int i = 0; i < 10; i++) s += lo_f(v[i]) + hi_f(v[i]);
  s = quad_sum(s);
  float mean = s * (1.f / 80.f);
  float q = 0.f;
#pragma unroll
  for (int i = 0; i < 10; i++) { float a = lo_f(v[i]) - mean, b = hi_f(v[i]) - mean; q += a * a; q += b * b; }
  q = quad_sum(q);
  return make_float2(mean, q);
}
__device__ __forceinline__ float2 combine_stats(float m0, float q0, float m1, float q1) {
  float mean = quad_sum(m0 + m1) * 0.125f;
  float d0 = m0 - mean, d1 = m1 - mean;
  float q = quad_sum(q0 + q1 + 80.f * (d0 * d0 + d1 * d1));
  return make_float2(mean, q * (1.f / 640.f));
}

__device__ __forceinline__ void feature_map(const float (&t)[20], float rl, uint32_t (&o)[20]) {
  float mx = t[0], mn = t[0];
#pragma unroll
  for (int i = 1; i < 20; i++) { mx = fmaxf(mx, t[i]); mn = fminf(mn, t[i]); }
  float bp = -mx * rl, bn = mn * rl;
  float ep[20], en[20];
  float sp = 0.f, sn = 0.f;
#pragma unroll
  for (int i = 0; i < 20; i++) {
    ep[i] = ex2(fmaf(t[i], rl, bp)); sp += ep[i];
    en[i] = ex2(fmaf(t[i], -rl, bn)); sn += en[i];
  }
  float ip = rcp(sp), in = rcp(sn);
#pragma unroll
  for (int i = 0; i < 10; i++) {
    o[i] = pack2(ep[2 * i] * ip, ep[2 * i + 1] * ip);
    o[10 + i] = pack2(en[2 * i] * in, en[2 * i + 1] * in);
  }
}

__device__ __forceinline__ void ld_row20(const __nv_bfloat16* p, uint32_t (&v)[10]) {
#pragma unroll
  for (int i = 0; i < 5; i++) { uint2 t = __ldg(reinterpret_cast<const uint2*>(p) + i); v[2 * i] = t.x; v[2 * i + 1] = t.y; }
}
__device__ __forceinline__ void sts_row20(uint32_t a, const uint32_t (&v)[10]) {
#pragma unroll
  for (int i = 0; i < 5; i++) sts64(a + i * 8, v[2 * i], v[2 * i + 1]);
}
__device__ __forceinline__ void warp_store(const CUtensorMap* m, int c0, int c1, uint32_t src, int lane) {
  fence_async_smem();
  __syncwarp();
  if (lane == 0) { tma_store2d(m, c0, c1, src); bulk_commit_wait(); }
  __syncwarp();
}

__global__ void __launch_bounds__(NTHREADS, 1)
fused_kernel(const __grid_constant__ CUtensorMap tm_x, const __grid_constant__ CUtensorMap tm_act,
             const __grid_constant__ CUtensorMap tm_wts, const __grid_constant__ CUtensorMap tm_u,
             const __grid_constant__ CUtensorMap tm_w1, const __grid_constant__ CUtensorMap tm_w2,
             const __grid_constant__ CUtensorMap ts_buf, const __grid_constant__ CUtensorMap ts_out,
             const __grid_constant__ CUtensorMap ts_u, const Params prm) {
  extern __shared__ __align__(1024) uint8_t smem[];
  const uint32_t sb = smem_u32(smem);
  const int tid = threadIdx.x, warp = __shfl_sync(0xffffffffu, tid >> 5, 0), lane = tid & 31;
  const int c = blockIdx.x;
  const int mt = c >> 3, g = c & 7;
  const bool b1_on = (c & 15) < 15;
  const int dt = (c & 15) % 5, ft = (c >> 4) * 3 + (c & 15) / 5;
  auto FULL = [&](int i) { return sb + SM_BARS + 8 * i; };
  auto EMPTY = [&](int i) { return sb + SM_BARS + 8 * (B_EMPTY + i); };

  if (tid == 0) {
    *reinterpret_cast<volatile int*>(smem + SM_ABORT) = 0;
    for (int i = 0; i < B_NRING; i++) { mbar_init(FULL(i), 1); mbar_init(EMPTY(i), 2); }
    mbar_init(FULL(B_MLDONE), 2);
    mbar_init(FULL(B_KVRDY), 1);
    asm volatile("fence.mbarrier_init.release.cluster;" ::: "memory");
  }
  __syncthreads();
  unsigned epoch;
  asm volatile("ld.relaxed.gpu.global.u32 %0, [%1];" : "=r"(epoch) : "l"(&g_epoch) : "memory");
  const unsigned ep1 = epoch + 1;

  if (warp >= 8) {
    asm volatile("setmaxnreg.dec.sync.aligned.u32 40;");
    if (warp == 8) {
      Pos<P1_NA> r1; Pos<P3_NA> r3; Pos<P4_NA> r4; Pos<P5_NB> r5;
      uint32_t mlph = 0;
      for (int layer = 0; layer < 2; layer++) {
        if (lane == 0) {
          if (layer) { mbar_wait(FULL(B_MLDONE), mlph); mlph ^= 1; wait_cnt(C_X + mt, ep1 * 8); fence_async_global(); }
          const CUtensorMap* tm = layer ? &tm_act : &tm_x;
          const int xrow = (layer ? R_X2 : 0) + mt * 128;
          for (int it = 0; it < 20; it++) {
            int kb = it >= 10 ? it - 10 : it;
            mbar_wait(EMPTY(B_P1A + r1.slot), r1.ph ^ 1);
            uint32_t bar = FULL(B_P1A + r1.slot), dst = sb + P1_A + r1.slot * 16384;
            mbar_expect(bar, 16384);
            tma2d(dst, tm, kb * 64, xrow, bar);
            tma2d(dst + 8192, tm, kb * 64, xrow + 64, bar);
            r1.next();
          }
          mbar_wait(FULL(B_MLDONE), mlph); mlph ^= 1;
          wait_cnt(C_O + layer * 16 + mt, ep1 * 8); fence_async_global();
          for (int kb = 0; kb < 10; kb++) {
            mbar_wait(EMPTY(B_P3A + r3.slot), r3.ph ^ 1);
            uint32_t bar = FULL(B_P3A + r3.slot), dst = sb + P3_A + r3.slot * 16384;
            mbar_expect(bar, 16384);
            tma2d(dst, &tm_act, kb * 64, R_O + mt * 128, bar);
            tma2d(dst + 8192, &tm_act, kb * 64, R_O + mt * 128 + 64, bar);
            r3.next();
          }
          mbar_wait(FULL(B_MLDONE), mlph); mlph ^= 1;
        }
        __syncwarp();
        if (b1_on) {
          if (lane < 16) wait_cnt(C_H + layer * 16 + lane, ep1 * 8);
          __syncwarp();
          if (lane == 0) {
            if (layer == 1 && c == 0) g_epoch = ep1;
            fence_async_global();
            for (int kb = 0; kb < 32; kb++) {
              mbar_wait(EMPTY(B_P4A + r4.slot), r4.ph ^ 1);
              uint32_t bar = FULL(B_P4A + r4.slot), dst = sb + P4_A + r4.slot * 16384;
              mbar_expect(bar, 16384);
              tma2d(dst, &tm_act, dt * 128, R_H + kb * 64, bar);
              tma2d(dst + 8192, &tm_act, dt * 128 + 64, R_H + kb * 64, bar);
              r4.next();
            }
            mbar_wait(FULL(B_MLDONE), mlph); mlph ^= 1;
          }
          __syncwarp();
        }
        {
          int dlo = (80 * g) >> 7, dhi = (80 * g + 79) >> 7;
          if (lane == 0) wait_cnt(C_U + layer * 5 + dlo, ep1 * 24);
          if (lane == 1) wait_cnt(C_U + layer * 5 + dhi, ep1 * 24);
          __syncwarp();
        }
        if (lane == 0) {
          fence_async_global();
          for (int kb = 0; kb < 24; kb++) {
            mbar_wait(EMPTY(B_P5B + r5.slot), r5.ph ^ 1);
            uint32_t bar = FULL(B_P5B + r5.slot), dst = sb + P5_B + r5.slot * 10240;
            mbar_expect(bar, 10240);
            tma5d(dst, &tm_u, kb * 64, g, bar);
            r5.next();
          }
        }
        __syncwarp();
      }
    } else if (warp == 9) {
      if (lane == 0) {
        Pos<P1_NB> r1; Pos<P4_NB> r4; Pos<P5_NA> r5;
        uint32_t mlph = 0;
        for (int layer = 0; layer < 2; layer++) {
          if (layer) { mbar_wait(FULL(B_MLDONE), mlph); mlph ^= 1; }
          else { wait_cnt(C_P0, ep1 * NCTA); fence_async_global(); }
          for (int it = 0; it < 30; it++) {
            int kb = it < 20 ? (it >> 1) : it - 20;
            int row = g * 240 + (it < 20 ? (it & 1) * 80 : 160);
            mbar_wait(EMPTY(B_P1B + r1.slot), r1.ph ^ 1);
            uint32_t bar = FULL(B_P1B + r1.slot);
            mbar_expect(bar, 10240);
            tma2d(sb + P1_B + r1.slot * 10240, &tm_wts, kb * 64, row, bar);
            r1.next();
          }
          mbar_wait(FULL(B_MLDONE), mlph); mlph ^= 1;
          for (int kb = 0; kb < 10; kb++) {
            uint32_t bar = FULL(B_P3B + kb);
            mbar_expect(bar, 10240);
            tma2d(sb + P3_B + kb * 10240, &tm_wts, kb * 64, R_WO + g * 80, bar);
          }
          mbar_wait(FULL(B_MLDONE), mlph); mlph ^= 1;
          if (b1_on) {
            for (int kb = 0; kb < 32; kb++) {
              mbar_wait(EMPTY(B_P4B + r4.slot), r4.ph ^ 1);
              uint32_t bar = FULL(B_P4B + r4.slot);
              mbar_expect(bar, 8192);
              tma2d(sb + P4_B + r4.slot * 8192, &tm_w1, ft * 64, kb * 64, bar);
              r4.next();
            }
            mbar_wait(FULL(B_MLDONE), mlph); mlph ^= 1;
          }
          for (int kb = 0; kb < 24; kb++) {
            mbar_wait(EMPTY(B_P5A + r5.slot), r5.ph ^ 1);
            uint32_t bar = FULL(B_P5A + r5.slot), dst = sb + P5_A + r5.slot * 16384;
            mbar_expect(bar, 16384);
            tma2d(dst, &tm_w2, mt * 128, kb * 64, bar);
            tma2d(dst + 8192, &tm_w2, mt * 128 + 64, kb * 64, bar);
            r5.next();
          }
        }
      }
    } else if (warp == 10) {
      bar_sync(BAR_SIG, 288);
      if (lane == 0) red_rel(&g_cnt[C_P0 * 32]);
      for (int layer = 0; layer < 2; layer++) {
        bar_sync(BAR_SIG, 288);
        if (lane == 0) {
          red_rel(&g_cnt[(C_KV + layer * 8 + g) * 32]);
          wait_cnt(C_KV + layer * 8 + g, ep1 * 16);
          mbar_arrive(FULL(B_KVRDY));
        }
        __syncwarp();
        bar_sync(BAR_SIG, 288);
        if (lane == 0) red_rel(&g_cnt[(C_O + layer * 16 + mt) * 32]);
        __syncwarp();
        bar_sync(BAR_SIG, 288);
        if (lane == 0) red_rel(&g_cnt[(C_H + layer * 16 + mt) * 32]);
        __syncwarp();
        if (b1_on) {
          bar_sync(BAR_SIG2, 288);
          if (lane == 0) red_rel(&g_cnt[(C_U + layer * 5 + dt) * 32]);
          __syncwarp();
        }
        if (layer == 0) {
          bar_sync(BAR_SIG, 288);
          if (lane == 0) red_rel(&g_cnt[(C_X + mt) * 32]);
          __syncwarp();
        }
      }
    } else {
      if (lane < 8) {
        const char* p1 = reinterpret_cast<const char*>(prm.w1) + (size_t)c * 49152 + (lane & 3) * 12288;
        const char* p2 = reinterpret_cast<const char*>(prm.w2) + (size_t)c * 49152 + (lane & 3) * 12288;
        wait_cnt(C_P0, ep1 * NCTA);
        l2_prefetch(lane < 4 ? p1 : p2, 12288);
      }
    }
  } else {
    asm volatile("setmaxnreg.inc.sync.aligned.u32 232;");
    const int wg = warp >> 2, wq = warp & 3, gq = lane >> 2, j = lane & 3;
    const bool elect = (tid & 127) == 0;
    const int lrow = wg * 64 + wq * 16 + gq;
    const int grow = mt * 128 + lrow;
    uint32_t xr[2][10];

    const uint32_t st_w = sb + SM_ST + warp * 2560;
    const uint32_t st_t = st_w + gq * 160 + j * 40;
    {
      const int kblk = c >> 4, type = (c >> 2) & 3, hh = (c & 3) * 8 + warp;
      const __nv_bfloat16* src = type < 3 ? prm.wqkv + type * 640 + hh * 20 : prm.wo + hh * 20;
      const int ld = type < 3 ? 1920 : 640;
      uint32_t b[10][3];
#pragma unroll
      for (int t = 0; t < 10; t++) {
        const uint32_t* p = reinterpret_cast<const uint32_t*>(src + (size_t)(kblk * 80 + t * 8 + gq) * ld);
        b[t][0] = __ldg(p + j); b[t][1] = __ldg(p + j + 4); b[t][2] = j < 2 ? __ldg(p + j + 8) : 0u;
      }
      const unsigned short* ph = reinterpret_cast<const unsigned short*>(prm.wphi) + hh * 400;
      auto aval = [&](int f, int d) -> uint32_t {
        if (f >= 20 || d >= 20) return 0u;
        if (type < 2) return (uint32_t)__ldg(ph + d * 20 + f);
        return f == d ? 0x3f80u : 0u;
      };
      auto apair = [&](int f, int d) -> uint32_t { return aval(f, d) | (aval(f, d + 1) << 16); };
      uint32_t a00[4] = {apair(gq, 2 * j), apair(gq + 8, 2 * j), apair(gq, 2 * j + 8), apair(gq + 8, 2 * j + 8)};
      uint32_t a01[4] = {apair(gq, 16 + 2 * j), apair(gq + 8, 16 + 2 * j), 0u, 0u};
      uint32_t a10[4] = {apair(16 + gq, 2 * j), 0u, apair(16 + gq, 2 * j + 8), 0u};
      uint32_t a11[4] = {apair(16 + gq, 16 + 2 * j), 0u, 0u, 0u};
      uint32_t xs[2][10];
      ld_row20(prm.x + (size_t)(c * 16 + warp * 2) * 640 + lane * 20, xs[0]);
      ld_row20(prm.x + (size_t)(c * 16 + warp * 2 + 1) * 640 + lane * 20, xs[1]);
      ld_row20(prm.x + (size_t)grow * 640 + g * 80 + j * 20, xr[0]);
      ld_row20(prm.x + (size_t)(grow + 8) * 640 + g * 80 + j * 20, xr[1]);
      if (tid < 210) reinterpret_cast<float2*>(&g_kv[0][0])[c * 210 + tid] = make_float2(0.f, 0.f);
      auto lr = [&](int f) { return (warp >> 2) * 80 + 8 * (f >> 1) + 2 * (warp & 3) + (f & 1); };
      const uint32_t s0 = sb + P1_STG + lr(gq) * 160 + j * 4, s1 = sb + P1_STG + lr(gq + 8) * 160 + j * 4,
                     s2 = sb + P1_STG + lr(16 + (gq & 3)) * 160 + j * 4;
      float cs0 = 0.f, cs1 = 0.f, cs2 = 0.f;
#pragma unroll
      for (int t = 0; t < 10; t++) {
        float c0[4] = {0.f, 0.f, 0.f, 0.f}, c1[4] = {0.f, 0.f, 0.f, 0.f};
        mma16816(c0, a00, b[t][0], b[t][1]);
        mma16816(c0, a01, b[t][2], 0u);
        mma16816(c1, a10, b[t][0], b[t][1]);
        mma16816(c1, a11, b[t][2], 0u);
        uint32_t p0 = pack2(c0[0], c0[1]), p1 = pack2(c0[2], c0[3]), p2 = pack2(c1[0], c1[1]);
        sts32(s0 + t * 16, p0); sts32(s1 + t * 16, p1);
        if (gq < 4) sts32(s2 + t * 16, p2);
        cs0 += lo_f(p0) + hi_f(p0); cs1 += lo_f(p1) + hi_f(p1); cs2 += lo_f(p2) + hi_f(p2);
      }
      fence_async_smem();
      bar_sync(BAR_CONS, 256);
      const int hg = (c & 3) * 2;
      auto grow_of = [&](int half) { return type < 3 ? (hg + half) * 240 + (type == 0 ? 160 : (type == 1 ? 0 : 80)) : R_WO + (hg + half) * 80; };
      if (lane == 0) {
        tma_store2d(&ts_buf, kblk * 80, grow_of(warp >= 5) + (warp >= 5 ? warp - 5 : warp) * 16, sb + P1_STG + warp * 2560);
        if (warp < 2) tma_store2d(&ts_buf, kblk * 80, grow_of(1) + (3 + warp) * 16, sb + P1_STG + (8 + warp) * 2560);
        asm volatile("cp.async.bulk.commit_group;" ::: "memory");
      }
      cs0 = quad_sum(cs0); cs1 = quad_sum(cs1); cs2 = quad_sum(cs2);
      if (type < 3 && j == 0) {
        float* cp = &g_colsum[kblk * 1920 + grow_of(warp >> 2) - (warp >> 2) * 80];
        cp[lr(gq)] = cs0; cp[lr(gq + 8)] = cs1;
        if (gq < 4) cp[lr(16 + gq)] = cs2;
      }
#pragma unroll
      for (int r = 0; r < 2; r++) {
        float2 st = chunk_stats(xs[r]);
        if (j == 0) g_stats[0][(c * 16 + warp * 2 + r) * 8 + gq] = st;
      }
      if (lane == 0) asm volatile("cp.async.bulk.wait_group 0;" ::: "memory");
      __syncwarp();
      bar_arrive(BAR_SIG, 288);
      TS(1);
    }

    Pos<P1_NA> r1a; Pos<P1_NB> r1b; Pos<P3_NA> r3a; Pos<P4_NA> r4a; Pos<P4_NB> r4b; Pos<P5_NA> r5a; Pos<P5_NB> r5b;

    for (int layer = 0; layer < 2; layer++) {
      uint32_t phq[2][20];
      {
        float kvacc[80]; zero(kvacc);
        float mean[2] = {0.f, 0.f}, rl[2] = {0.f, 0.f};
        int pa = 0, pb = 0;
#pragma unroll 1
        for (int kb = 0; kb < 10; kb++) {
          mbar_wait(FULL(B_P1A + r1a.slot), r1a.ph);
          mbar_wait(FULL(B_P1B + r1b.slot), r1b.ph);
          mbar_wait(FULL(B_P1B + r1b.slot + 1), r1b.ph);
          uint64_t da = mkdesc(sb + P1_A + r1a.slot * 16384 + wg * 8192, 16, 1024);
          uint64_t db = mkdesc(sb + P1_B + r1b.slot * 10240, 16, 1024);
          wg_fence();
#pragma unroll
          for (int kk = 0; kk < 4; kk++) wgmma_ss_n160<0, 0>(kvacc, da + kk * 2, db + kk * 2, (kb | kk) != 0);
          wg_commit();
          if (kb == 0) {
            TS(2 + layer * 16);
#pragma unroll
            for (int r = 0; r < 2; r++) {
              float4 s = __ldcg(reinterpret_cast<const float4*>(&g_stats[layer][(grow + 8 * r) * 8 + 2 * j]));
              float2 mv = combine_stats(s.x, s.y, s.z, s.w);
              mean[r] = mv.x; rl[r] = rsqrtf(mv.y + 1e-5f);
            }
            if (layer == 0 && tid < 240) {
              float cs = 0.f;
#pragma unroll
              for (int w = 0; w < 8; w++) cs += __ldcg(&g_colsum[w * 1920 + g * 240 + tid]);
              reinterpret_cast<float*>(smem + SM_CS)[tid] = cs;
            }
          } else {
            wg_wait<1>();
            if (elect) { mbar_arrive(EMPTY(B_P1A + pa)); mbar_arrive(EMPTY(B_P1B + pb)); mbar_arrive(EMPTY(B_P1B + pb + 1)); }
          }
          pa = r1a.slot; pb = r1b.slot;
          r1a.next(); r1b.next(); r1b.next();
        }
        wg_wait<0>();
        if (elect) { mbar_arrive(EMPTY(B_P1A + pa)); mbar_arrive(EMPTY(B_P1B + pb)); mbar_arrive(EMPTY(B_P1B + pb + 1)); }
        if (layer == 0) bar_sync(BAR_CONS, 256);
        TS(3 + layer * 16);

        float qacc[40]; zero(qacc);
        Pos<P1_NA> ra = r1a; Pos<P1_NB> rb = r1b;
        auto q_issue = [&](int kb) {
          mbar_wait(FULL(B_P1A + r1a.slot), r1a.ph);
          mbar_wait(FULL(B_P1B + r1b.slot), r1b.ph);
          uint64_t da = mkdesc(sb + P1_A + r1a.slot * 16384 + wg * 8192, 16, 1024);
          uint64_t db = mkdesc(sb + P1_B + r1b.slot * 10240, 16, 1024);
          wg_fence();
#pragma unroll
          for (int kk = 0; kk < 4; kk++) wgmma_ss_n80<0, 0>(qacc, da + kk * 2, db + kk * 2, (kb | kk) != 0);
          wg_commit();
          r1a.next(); r1b.next();
        };
        auto q_release = [&]() {
          if (elect) { mbar_arrive(EMPTY(B_P1A + ra.slot)); mbar_arrive(EMPTY(B_P1B + rb.slot)); }
          ra.next(); rb.next();
        };
        const uint32_t cs_addr = sb + SM_CS + j * 8;
        const uint32_t stg = sb + P1_STG + (j >> 1) * 32768;
        const int sub = j & 1;
        q_issue(0); q_issue(1);
#pragma unroll
        for (int r = 0; r < 2; r++) {
          float t[20];
#pragma unroll
          for (int i = 0; i < 10; i++) {
            float2 cs = lds64f(cs_addr + i * 32);
            t[2 * i] = fmaf(-mean[r], cs.x, kvacc[i * 4 + 2 * r]);
            t[2 * i + 1] = fmaf(-mean[r], cs.y, kvacc[i * 4 + 2 * r + 1]);
          }
          uint32_t ph[20];
          feature_map(t, rl[r] * LOG2E, ph);
          const int row = lrow + 8 * r;
          const uint32_t rb0 = stg + row * 128, sw = gq;
#pragma unroll
          for (int ch = 0; ch < 5; ch++) {
            int cidx = 5 * sub + ch;
            uint32_t addr = cidx < 8 ? rb0 + ((cidx ^ sw) << 4) : rb0 + 16384 + (((cidx - 2) ^ sw) << 4);
            sts128(addr, ph[4 * ch], ph[4 * ch + 1], ph[4 * ch + 2], ph[4 * ch + 3]);
          }
          uint32_t vv[10];
#pragma unroll
          for (int i = 0; i < 10; i++) {
            float2 cs = lds64f(cs_addr + 320 + i * 32);
            vv[i] = pack2(fmaf(-mean[r], cs.x, kvacc[40 + i * 4 + 2 * r]) * rl[r], fmaf(-mean[r], cs.y, kvacc[40 + i * 4 + 2 * r + 1]) * rl[r]);
          }
          const uint32_t ab = rb0 + 16384;
          sts128(ab + (((3 * sub) ^ sw) << 4), vv[0], vv[1], vv[2], vv[3]);
          sts128(ab + (((3 * sub + 1) ^ sw) << 4), vv[4], vv[5], vv[6], vv[7]);
          sts128(ab + (((3 * sub + 2) ^ sw) << 4), vv[8], vv[9], 0x00003f80u, 0u);
          wg_wait<1>(); q_release(); q_issue(2 + r);
        }
        fence_async_smem();
        bar_sync(BAR_CONS, 256);
        TS(4 + layer * 16);
        {
          float dacc[40]; zero(dacc);
          const uint32_t pt = sb + P1_STG + wg * 32768;
          uint64_t da = mkdesc(pt + 16384, 16384, 1024);
          uint64_t db = mkdesc(pt, 16384 + 96, 1024);
          wg_fence();
#pragma unroll
          for (int kk = 0; kk < 8; kk++) wgmma_ss_n80<1, 1>(dacc, da + kk * 128, db + kk * 128, kk != 0);
          wg_commit();
          wg_wait<2>(); q_release(); q_issue(4);
          wg_wait<1>(); q_release();
#pragma unroll
          for (int r = 0; r < 2; r++) {
            int rho = wq * 16 + gq + 8 * r;
            int sr = rho >= 24, dd = rho - 24 * sr;
            if (dd <= 20) {
              float* dst = &g_kv[layer][(4 * g + 2 * wg + sr) * 840 + dd * 40 + 2 * j];
#pragma unroll
              for (int ii = 0; ii < 5; ii++) {
                float v0 = sr ? dacc[(5 + ii) * 4 + 2 * r] : dacc[ii * 4 + 2 * r];
                float v1 = sr ? dacc[(5 + ii) * 4 + 2 * r + 1] : dacc[ii * 4 + 2 * r + 1];
                red_add2(dst + ii * 8, v0, v1);
              }
            }
          }
          bar_arrive(BAR_SIG, 288);
          TS(5 + layer * 16);
        }
#pragma unroll 1
        for (int kb = 5; kb < 10; kb++) { q_issue(kb); wg_wait<1>(); q_release(); }
        wg_wait<0>(); q_release();
        if (elect) mbar_arrive(FULL(B_MLDONE));
        TS(6 + layer * 16);
#pragma unroll
        for (int r = 0; r < 2; r++) {
          float t[20];
#pragma unroll
          for (int i = 0; i < 10; i++) {
            float2 cs = lds64f(cs_addr + 640 + i * 32);
            t[2 * i] = fmaf(-mean[r], cs.x, qacc[i * 4 + 2 * r]);
            t[2 * i + 1] = fmaf(-mean[r], cs.y, qacc[i * 4 + 2 * r + 1]);
          }
          feature_map(t, rl[r] * LOG2E, phq[r]);
        }
      }
      {
        TS(7 + layer * 16);
        mbar_wait(FULL(B_KVRDY), layer);
        TS(8 + layer * 16);
        const float* kvp = &g_kv[layer][4 * g * 840];
        float2 kvv[7] = {};
#pragma unroll
        for (int it = 0; it < 7; it++) {
          int idx = tid + 256 * it;
          if (idx < 1680) {
            int nn = idx / 20, ch = idx - nn * 20;
            int hj = nn < 80 ? (nn & 7) >> 1 : nn - 80;
            int dim = nn < 80 ? 2 * (nn >> 3) + (nn & 1) : 20;
            kvv[it] = __ldcg(reinterpret_cast<const float2*>(kvp + hj * 840 + dim * 40 + 2 * ch));
          }
        }
#pragma unroll
        for (int it = 0; it < 7; it++) {
          int idx = tid + 256 * it;
          if (idx < 1680) {
            int nn = idx / 20, ch = idx - nn * 20;
            int hj = nn < 80 ? (nn & 7) >> 1 : nn - 80;
            int n = nn < 80 ? nn : 80 + 2 * hj;
            uint32_t v = pack2(kvv[it].x, kvv[it].y);
            uint32_t addr = sb + P1_STG + (ch >> 3) * 11264 + n * 128 + (((ch & 7) ^ (n & 7)) << 4);
            sts128(addr, hj == 0 ? v : 0u, hj == 1 ? v : 0u, hj == 2 ? v : 0u, hj == 3 ? v : 0u);
          }
        }
        fence_async_smem();
        bar_sync(BAR_CONS, 256);
        float oacc[44]; zero(oacc);
        wg_fence();
#pragma unroll
        for (int t = 0; t < 10; t++) {
          uint32_t a[4] = {phq[0][2 * t], phq[1][2 * t], phq[0][2 * t + 1], phq[1][2 * t + 1]};
          uint64_t db = mkdesc(sb + P1_STG + (t >> 2) * 11264 + (t & 3) * 32, 16, 1024);
          wgmma_rs_n88<0>(oacc, a, db, t != 0);
        }
        wg_commit();
        wg_wait<0>();
#pragma unroll
        for (int r = 0; r < 2; r++) {
          float inv = rcp(oacc[40 + 2 * r] + 1e-6f);
          uint32_t ov[10];
#pragma unroll
          for (int i = 0; i < 10; i++) ov[i] = pack2(oacc[i * 4 + 2 * r] * inv, oacc[i * 4 + 2 * r + 1] * inv);
          sts_row20(st_t + r * 1280, ov);
        }
        warp_store(&ts_buf, g * 80, R_O + mt * 128 + warp * 16, st_w, lane);
        bar_arrive(BAR_SIG, 288);
        TS(9 + layer * 16);
      }
      {
        float acc[40]; zero(acc);
        int pa = 0;
#pragma unroll 1
        for (int kb = 0; kb < 10; kb++) {
          mbar_wait(FULL(B_P3A + r3a.slot), r3a.ph);
          mbar_wait(FULL(B_P3B + kb), layer);
          uint64_t da = mkdesc(sb + P3_A + r3a.slot * 16384 + wg * 8192, 16, 1024);
          uint64_t db = mkdesc(sb + P3_B + kb * 10240, 16, 1024);
          wg_fence();
#pragma unroll
          for (int kk = 0; kk < 4; kk++) wgmma_ss_n80<0, 0>(acc, da + kk * 2, db + kk * 2, (kb | kk) != 0);
          wg_commit();
          if (kb) { wg_wait<1>(); if (elect) mbar_arrive(EMPTY(B_P3A + pa)); } else TS(10 + layer * 16);
          pa = r3a.slot; r3a.next();
        }
        wg_wait<0>();
        if (elect) { mbar_arrive(EMPTY(B_P3A + pa)); mbar_arrive(FULL(B_MLDONE)); }
        TS(11 + layer * 16);
        const unsigned tag = ep1;
#pragma unroll
        for (int r = 0; r < 2; r++) {
#pragma unroll
          for (int i = 0; i < 10; i++)
            xr[r][i] = pack2(lo_f(xr[r][i]) + acc[i * 4 + 2 * r], hi_f(xr[r][i]) + acc[i * 4 + 2 * r + 1]);
          float2 st = chunk_stats(xr[r]);
          if (j == r) st_vol4(&g_ll[layer][(grow + 8 * r) * 8 + g], make_uint4(__float_as_uint(st.x), tag, __float_as_uint(st.y), tag));
        }
        uint4 l[2][2];
        {
          int n = 0;
          bool ok;
          do {
#pragma unroll
            for (int r = 0; r < 2; r++) {
              l[r][0] = ld_vol4(&g_ll[layer][(grow + 8 * r) * 8 + 2 * j]);
              l[r][1] = ld_vol4(&g_ll[layer][(grow + 8 * r) * 8 + 2 * j + 1]);
            }
            ok = l[0][0].y == tag && l[0][0].w == tag && l[0][1].y == tag && l[0][1].w == tag &&
                 l[1][0].y == tag && l[1][0].w == tag && l[1][1].y == tag && l[1][1].w == tag;
            if (timed_out(++n)) break;
          } while (!ok);
        }
        __syncwarp();
#pragma unroll
        for (int r = 0; r < 2; r++) {
          float2 mv = combine_stats(__uint_as_float(l[r][0].x), __uint_as_float(l[r][0].z), __uint_as_float(l[r][1].x), __uint_as_float(l[r][1].z));
          float ve = mv.y + 1e-5f;
          float rr = rsqrtf(ve) * rsqrtf(mv.y / ve + 1e-5f);
          float nb = -mv.x * rr;
          uint32_t hv[10];
#pragma unroll
          for (int i = 0; i < 10; i++) hv[i] = pack2(fmaf(lo_f(xr[r][i]), rr, nb), fmaf(hi_f(xr[r][i]), rr, nb));
          sts_row20(st_t + r * 1280, hv);
        }
        warp_store(&ts_buf, g * 80, R_H + mt * 128 + warp * 16, st_w, lane);
        bar_arrive(BAR_SIG, 288);
        TS(12 + layer * 16);
      }
      if (b1_on) {
        float acc[32]; zero(acc);
        uint32_t bias[8];
#pragma unroll
        for (int i = 0; i < 8; i++) bias[i] = __ldg(reinterpret_cast<const uint32_t*>(prm.b1 + ft * 64 + i * 8) + j);
        int pa = 0, pb = 0;
#pragma unroll 1
        for (int kb = 0; kb < 32; kb++) {
          mbar_wait(FULL(B_P4A + r4a.slot), r4a.ph);
          mbar_wait(FULL(B_P4B + r4b.slot), r4b.ph);
          uint64_t da = mkdesc(sb + P4_A + r4a.slot * 16384 + wg * 8192, 8192, 1024);
          uint64_t db = mkdesc(sb + P4_B + r4b.slot * 8192, 8192, 1024);
          wg_fence();
#pragma unroll
          for (int kk = 0; kk < 4; kk++) wgmma_ss_n64<1, 1>(acc, da + kk * 128, db + kk * 128, (kb | kk) != 0);
          wg_commit();
          if (kb) { wg_wait<1>(); if (elect) { mbar_arrive(EMPTY(B_P4A + pa)); mbar_arrive(EMPTY(B_P4B + pb)); } } else TS(13 + layer * 16);
          pa = r4a.slot; pb = r4b.slot; r4a.next(); r4b.next();
        }
        wg_wait<0>();
        if (elect) { mbar_arrive(EMPTY(B_P4A + pa)); mbar_arrive(EMPTY(B_P4B + pb)); mbar_arrive(FULL(B_MLDONE)); }
        TS(14 + layer * 16);
#pragma unroll
        for (int r = 0; r < 2; r++) {
          const uint32_t dst = sb + SM_ST + warp * 2048 + (gq + 8 * r) * 128 + j * 4;
#pragma unroll
          for (int i = 0; i < 8; i++) {
            float v0 = acc[i * 4 + 2 * r] + lo_f(bias[i]), v1 = acc[i * 4 + 2 * r + 1] + hi_f(bias[i]);
            float t0 = tanh_a(v0 * fmaf(v0 * v0, 0.0356774081f, 0.7978845608f));
            float t1 = tanh_a(v1 * fmaf(v1 * v1, 0.0356774081f, 0.7978845608f));
            float h0 = 0.5f * v0, h1 = 0.5f * v1;
            sts32(dst + ((i ^ gq) << 4), pack2(fmaf(h0, t0, h0), fmaf(h1, t1, h1)));
          }
        }
        warp_store(&ts_u, ft * 64, dt * 128 + warp * 16, sb + SM_ST + warp * 2048, lane);
        bar_arrive(BAR_SIG2, 288);
      }
      {
        float acc[40]; zero(acc);
        float b2v[2];
        b2v[0] = __bfloat162float(prm.b2[grow]); b2v[1] = __bfloat162float(prm.b2[grow + 8]);
        int pa = 0, pb = 0;
#pragma unroll 1
        for (int kb = 0; kb < 24; kb++) {
          mbar_wait(FULL(B_P5A + r5a.slot), r5a.ph);
          mbar_wait(FULL(B_P5B + r5b.slot), r5b.ph);
          uint64_t da = mkdesc(sb + P5_A + r5a.slot * 16384 + wg * 8192, 8192, 1024);
          uint64_t db = mkdesc(sb + P5_B + r5b.slot * 10240, 16, 1024);
          wg_fence();
#pragma unroll
          for (int kk = 0; kk < 4; kk++) wgmma_ss_n80<1, 0>(acc, da + kk * 128, db + kk * 2, (kb | kk) != 0);
          wg_commit();
          if (kb) { wg_wait<1>(); if (elect) { mbar_arrive(EMPTY(B_P5A + pa)); mbar_arrive(EMPTY(B_P5B + pb)); } } else TS(15 + layer * 16);
          pa = r5a.slot; pb = r5b.slot; r5a.next(); r5b.next();
        }
        wg_wait<0>();
        if (elect) { mbar_arrive(EMPTY(B_P5A + pa)); mbar_arrive(EMPTY(B_P5B + pb)); mbar_arrive(FULL(B_MLDONE)); }
        TS(16 + layer * 16);
#pragma unroll
        for (int r = 0; r < 2; r++) {
#pragma unroll
          for (int i = 0; i < 10; i++)
            xr[r][i] = pack2(lo_f(xr[r][i]) + (acc[i * 4 + 2 * r] + b2v[r]), hi_f(xr[r][i]) + (acc[i * 4 + 2 * r + 1] + b2v[r]));
          sts_row20(st_t + r * 1280, xr[r]);
          if (layer == 0) {
            float2 st = chunk_stats(xr[r]);
            if (j == r) g_stats[1][(grow + 8 * r) * 8 + g] = st;
          }
        }
        warp_store(layer ? &ts_out : &ts_buf, g * 80, (layer ? 0 : R_X2) + mt * 128 + warp * 16, st_w, lane);
        if (layer == 0) bar_arrive(BAR_SIG, 288);
        TS(17 + layer * 16);
      }
    }
  }
}

typedef CUresult (*EncodeFn)(CUtensorMap*, CUtensorMapDataType, cuuint32_t, void*, const cuuint64_t*, const cuuint64_t*,
                             const cuuint32_t*, const cuuint32_t*, CUtensorMapInterleave, CUtensorMapSwizzle,
                             CUtensorMapL2promotion, CUtensorMapFloatOOBfill);

void make_map(EncodeFn fn, CUtensorMap* m, const void* base, uint64_t cols, uint64_t rows, uint32_t box_cols, uint32_t box_rows, bool swz) {
  cuuint64_t dims[2] = {cols, rows};
  cuuint64_t strides[1] = {cols * 2};
  cuuint32_t box[2] = {box_cols, box_rows};
  cuuint32_t es[2] = {1, 1};
  fn(m, CU_TENSOR_MAP_DATA_TYPE_BFLOAT16, 2, const_cast<void*>(base), dims, strides, box, es, CU_TENSOR_MAP_INTERLEAVE_NONE,
     swz ? CU_TENSOR_MAP_SWIZZLE_128B : CU_TENSOR_MAP_SWIZZLE_NONE, CU_TENSOR_MAP_L2_PROMOTION_L2_256B, CU_TENSOR_MAP_FLOAT_OOB_FILL_NONE);
}

}

extern "C" void kernel_launch(void* const* d_in, const int* in_sizes, int n_in, void* d_out, int out_size) {
  static bool init = false;
  static CUtensorMap tm_x, tm_act, tm_wts, tm_u, tm_w1, tm_w2, ts_buf, ts_out, ts_u;
  static const void* cached[4] = {nullptr, nullptr, nullptr, nullptr};
  if (!init || cached[0] != d_in[0] || cached[1] != d_in[5] || cached[2] != d_in[7] || cached[3] != d_out) {
    void* fnp = nullptr;
    cudaDriverEntryPointQueryResult qr;
    cudaGetDriverEntryPoint("cuTensorMapEncodeTiled", &fnp, cudaEnableDefault, &qr);
    EncodeFn fn = (EncodeFn)fnp;
    void *p_buf, *p_u;
    cudaGetSymbolAddress(&p_buf, g_buf);
    cudaGetSymbolAddress(&p_u, g_u);
    make_map(fn, &tm_x, d_in[0], 640, 2048, 64, 64, true);
    make_map(fn, &tm_act, p_buf, 640, R_END, 64, 64, true);
    make_map(fn, &tm_wts, p_buf, 640, R_END, 64, 80, true);
    make_map(fn, &tm_w1, d_in[5], 1536, 2048, 64, 64, true);
    make_map(fn, &tm_w2, d_in[7], 2048, 1536, 64, 64, true);
    make_map(fn, &ts_buf, p_buf, 640, R_END, 80, 16, false);
    make_map(fn, &ts_out, d_out, 640, 2048, 80, 16, false);
    make_map(fn, &ts_u, p_u, 1536, 640, 64, 16, true);
    {
      cuuint64_t dims[5] = {1536, 2, 4, 10, 8};
      cuuint64_t strides[4] = {3072, 20 * 3072, 2 * 3072, 80 * 3072};
      cuuint32_t box[5] = {64, 2, 4, 10, 1};
      cuuint32_t es[5] = {1, 1, 1, 1, 1};
      fn(&tm_u, CU_TENSOR_MAP_DATA_TYPE_BFLOAT16, 5, p_u, dims, strides, box, es, CU_TENSOR_MAP_INTERLEAVE_NONE,
         CU_TENSOR_MAP_SWIZZLE_128B, CU_TENSOR_MAP_L2_PROMOTION_L2_256B, CU_TENSOR_MAP_FLOAT_OOB_FILL_NONE);
    }
    cudaFuncSetAttribute(fused_kernel, cudaFuncAttributeMaxDynamicSharedMemorySize, SM_TOTAL);
    cached[0] = d_in[0]; cached[1] = d_in[5]; cached[2] = d_in[7]; cached[3] = d_out;
    init = true;
  }
  Params p;
  p.x = (const __nv_bfloat16*)d_in[0];
  p.wqkv = (const __nv_bfloat16*)d_in[1];
  p.wphi = (const __nv_bfloat16*)d_in[2];
  p.wo = (const __nv_bfloat16*)d_in[3];
  p.w1 = (const __nv_bfloat16*)d_in[5];
  p.b1 = (const __nv_bfloat16*)d_in[6];
  p.w2 = (const __nv_bfloat16*)d_in[7];
  p.b2 = (const __nv_bfloat16*)d_in[8];
  p.out = (__nv_bfloat16*)d_out;
  fused_kernel<<<NCTA, NTHREADS, SM_TOTAL>>>(tm_x, tm_act, tm_wts, tm_u, tm_w1, tm_w2, ts_buf, ts_out, ts_u, p);
}
```

```cpp
#include <cuda_runtime.h>
#include <cuda_bf16.h>
#include <cuda.h>
#include <stdint.h>

namespace {

constexpr int NCTA = 128;
constexpr int NTHREADS = 384;

constexpr int R_WQKV = 0, R_WO = 1920, R_X2 = 2560, R_O = R_X2 + 2048, R_H = R_O + 2048, R_END = R_H + 2048;
__device__ __align__(1024) __nv_bfloat16 g_buf[R_END * 640];
__device__ __align__(1024) __nv_bfloat16 g_u[640 * 1536];
constexpr int Z_KV = 0, Z_END = 2 * 32 * 840;
__device__ __align__(16) float g_acc[Z_END];
__device__ __align__(128) uint2 g_ll[4 * 16384];
constexpr int C_P0 = 0, C_W = 1, C_WO = C_W + 8, C_KV = C_WO + 8, C_O = C_KV + 16, C_H = C_O + 64, C_U = C_H + 32, C_X = C_U + 10,
              C_NUM = C_X + 16;
__device__ __align__(128) unsigned g_cnt[C_NUM * 32];
__device__ unsigned g_epoch;

#define TS(i) do {} while (0)
#define TSB(i) do {} while (0)

constexpr int KB = 1024;
constexpr int SM_MISC = 224 * KB;
constexpr int SM_BARS = SM_MISC;
constexpr int SM_CS = SM_MISC + 1280;
constexpr int SM_ABORT = SM_CS + 960, SM_CNT = SM_ABORT + 4;
constexpr int SM_ST = 204 * KB;
constexpr int SM_TOTAL = 227 * KB;
constexpr int P1_NA = 5, P1_NB = 4, P1_A = 0, P1_B = 80 * KB, P1_STG = 160 * KB;
constexpr int P3_NA = 6, P3_NB = 5, P3_B = 0, P3_A = 100 * KB;
constexpr int P4_NA = 8, P4_NB = 9, P4_B = 0, P4_A = 72 * KB;
constexpr int P5_NA = P4_NA, P5_NB = 7, P5_A = P4_A, P5_B = 0;
constexpr int B_P1A = 0, B_P1B = B_P1A + P1_NA, B_P3A = B_P1B + P1_NB, B_P3B = B_P3A + P3_NA, B_P4A = B_P3B + P3_NB,
              B_P4B = B_P4A + P4_NA, B_P5A = B_P4A, B_P5B = B_P4B + P4_NB, B_NRING = B_P5B + P5_NB;
constexpr int B_EMPTY = 68;
constexpr int B_MLDONE = 136, B_KVRDY = 137, B_STAT = 138, B_P0 = 139, B_ODONE = 140, B_FLO = 141, B_FLH = 142;
constexpr int P2_B = P1_STG + 10 * KB;

#define P4_DT(c) (((c) & 15) % 5)
#define P4_FT(c) (((c) >> 4) * 3 + ((c) & 15) / 5)

#define POLL_NS 0
__device__ __forceinline__ uint32_t smem_u32(const void* p) { return (uint32_t)__cvta_generic_to_shared(p); }
__device__ __forceinline__ void mbar_init(uint32_t a, int c) { asm volatile("mbarrier.init.shared::cta.b64 [%0], %1;" ::"r"(a), "r"(c)); }
__device__ __forceinline__ void mbar_expect(uint32_t a, int bytes) {
  asm volatile("mbarrier.arrive.expect_tx.shared::cta.b64 _, [%0], %1;" ::"r"(a), "r"(bytes) : "memory");
}
__device__ __forceinline__ void mbar_arrive(uint32_t a) { asm volatile("mbarrier.arrive.shared::cta.b64 _, [%0];" ::"r"(a) : "memory"); }
__device__ __forceinline__ bool mbar_try(uint32_t a, uint32_t ph) {
  uint32_t ok;
  asm volatile("{\n.reg .pred p;\nmbarrier.try_wait.parity.shared::cta.b64 p, [%1], %2;\nselp.u32 %0, 1, 0, p;\n}" : "=r"(ok) : "r"(a), "r"(ph) : "memory");
  return ok;
}
__device__ __forceinline__ bool mbar_test(uint32_t a, uint32_t ph) {
  uint32_t ok;
  asm volatile("{\n.reg .pred p;\nmbarrier.test_wait.parity.shared::cta.b64 p, [%1], %2;\nselp.u32 %0, 1, 0, p;\n}" : "=r"(ok) : "r"(a), "r"(ph) : "memory");
  return ok;
}
__device__ __forceinline__ bool timed_out(int n) {
  if (n & 255) return false;
  extern __shared__ __align__(1024) uint8_t smem_raw[];
  volatile int* ab = reinterpret_cast<volatile int*>(smem_raw + SM_ABORT);
  if (n > (1 << 21)) *ab = 1;
  return *ab != 0;
}
__device__ __forceinline__ void mbar_wait(uint32_t a, uint32_t ph) {
  if (mbar_try(a, ph)) return;
  int n = 0;
  while (!mbar_try(a, ph)) { if (timed_out(++n)) break; }
}
__device__ __forceinline__ void tma2d(uint32_t dst, const CUtensorMap* m, int c0, int c1, uint32_t bar) {
  asm volatile("cp.async.bulk.tensor.2d.shared::cluster.global.mbarrier::complete_tx::bytes [%0], [%1, {%3, %4}], [%2];"
               ::"r"(dst), "l"(m), "r"(bar), "r"(c0), "r"(c1) : "memory");
}
__device__ __forceinline__ void tma2d_prefetch(const CUtensorMap* m, int c0, int c1) {
  asm volatile("cp.async.bulk.prefetch.tensor.2d.L2.global [%0, {%1, %2}];" ::"l"(m), "r"(c0), "r"(c1) : "memory");
}
__device__ __forceinline__ void tma3d(uint32_t dst, const CUtensorMap* m, int c1, int c2, uint32_t bar) {
  asm volatile("cp.async.bulk.tensor.3d.shared::cluster.global.mbarrier::complete_tx::bytes [%0], [%1, {%5, %3, %4}], [%2];"
               ::"r"(dst), "l"(m), "r"(bar), "r"(c1), "r"(c2), "r"(0) : "memory");
}
__device__ __forceinline__ bool elect_one() {
  uint32_t p;
  asm volatile("{\n.reg .pred P;\nelect.sync _|P, 0xffffffff;\nselp.u32 %0, 1, 0, P;\n}" : "=r"(p));
  return p;
}
__device__ __forceinline__ void tma5d(uint32_t dst, const CUtensorMap* m, int c0, int c4, uint32_t bar) {
  asm volatile("cp.async.bulk.tensor.5d.shared::cluster.global.mbarrier::complete_tx::bytes [%0], [%1, {%3, %5, %5, %5, %4}], [%2];"
               ::"r"(dst), "l"(m), "r"(bar), "r"(c0), "r"(c4), "r"(0) : "memory");
}
__device__ __forceinline__ void tma_store2d(const CUtensorMap* m, int c0, int c1, uint32_t src) {
  asm volatile("cp.async.bulk.tensor.2d.global.shared::cta.bulk_group [%0, {%2, %3}], [%1];" ::"l"(m), "r"(src), "r"(c0), "r"(c1) : "memory");
}
__device__ __forceinline__ void tma_store4d(const CUtensorMap* m, int c0, int c2, int c3, uint32_t src) {
  asm volatile("cp.async.bulk.tensor.4d.global.shared::cta.bulk_group [%0, {%2, %5, %3, %4}], [%1];" ::"l"(m), "r"(src), "r"(c0), "r"(c2), "r"(c3), "r"(0) : "memory");
}
__device__ __forceinline__ void bulk_redadd(float* dst, uint32_t src, int bytes) {
  asm volatile("cp.reduce.async.bulk.global.shared::cta.bulk_group.add.f32 [%0], [%1], %2;" ::"l"(dst), "r"(src), "r"(bytes) : "memory");
}
__device__ __forceinline__ void bulk_load(uint32_t dst, const void* src, int bytes, uint32_t bar) {
  asm volatile("cp.async.bulk.shared::cluster.global.mbarrier::complete_tx::bytes [%0], [%1], %2, [%3];" ::"r"(dst), "l"(src), "r"(bytes), "r"(bar) : "memory");
}
__device__ __forceinline__ void bulk_store(void* dst, uint32_t src, int bytes) {
  asm volatile("cp.async.bulk.global.shared::cta.bulk_group [%0], [%1], %2;" ::"l"(dst), "r"(src), "r"(bytes) : "memory");
}
__device__ __forceinline__ void st_ll(uint2* p, uint32_t a, uint32_t b) {
  asm volatile("{\n.reg .b64 t;\nmov.b64 t, {%1, %2};\nst.relaxed.gpu.global.b64 [%0], t;\n}" ::"l"(p), "r"(a), "r"(b) : "memory");
}
__device__ __forceinline__ uint4 ld_ll(const uint2* p) {
  uint4 v;
  asm volatile("{\n.reg .b64 t, u;\nld.relaxed.gpu.global.v2.b64 {t, u}, [%4];\nmov.b64 {%0, %1}, t;\nmov.b64 {%2, %3}, u;\n}"
               : "=r"(v.x), "=r"(v.y), "=r"(v.z), "=r"(v.w) : "l"(p) : "memory");
  return v;
}
__device__ __forceinline__ void bulk_commit_wait() {
  asm volatile("cp.async.bulk.commit_group;\ncp.async.bulk.wait_group 0;" ::: "memory");
}
__device__ __forceinline__ void sts64(uint32_t a, uint32_t x, uint32_t y) {
  asm volatile("st.shared.v2.b32 [%0], {%1, %2};" ::"r"(a), "r"(x), "r"(y) : "memory");
}
__device__ __forceinline__ void sts32(uint32_t a, uint32_t x) { asm volatile("st.shared.b32 [%0], %1;" ::"r"(a), "r"(x) : "memory"); }
__device__ __forceinline__ void l2_prefetch(const void* p, int bytes) {
  asm volatile("cp.async.bulk.prefetch.L2.global [%0], %1;" ::"l"(p), "r"(bytes) : "memory");
}
__device__ __forceinline__ unsigned ld_acq(const unsigned* p) {
  unsigned v; asm volatile("ld.relaxed.gpu.global.u32 %0, [%1];" : "=r"(v) : "l"(p) : "memory"); return v;
}
__device__ __forceinline__ void red_rel(unsigned* p) { asm volatile("red.release.gpu.global.add.u32 [%0], 1;" ::"l"(p) : "memory"); }
__device__ __forceinline__ void red_rlx(unsigned* p) { asm volatile("red.relaxed.gpu.global.add.u32 [%0], 1;" ::"l"(p) : "memory"); }
__device__ __forceinline__ void fence_gpu() { asm volatile("fence.acq_rel.gpu;" ::: "memory"); }
__device__ __forceinline__ void prefetch_map(const CUtensorMap* m) { asm volatile("prefetch.tensormap [%0];" ::"l"(m) : "memory"); }
__device__ __forceinline__ uint32_t lds32(uint32_t a) { uint32_t v; asm volatile("ld.shared.b32 %0, [%1];" : "=r"(v) : "r"(a)); return v; }
__device__ __forceinline__ uint4 lds128(uint32_t a) {
  uint4 v; asm volatile("ld.shared.v4.b32 {%0, %1, %2, %3}, [%4];" : "=r"(v.x), "=r"(v.y), "=r"(v.z), "=r"(v.w) : "r"(a)); return v;
}
__device__ __forceinline__ float4 lds128f(uint32_t a) {
  float4 v; asm volatile("ld.shared.v4.f32 {%0, %1, %2, %3}, [%4];" : "=f"(v.x), "=f"(v.y), "=f"(v.z), "=f"(v.w) : "r"(a)); return v;
}
__device__ __forceinline__ void ldsm4t(uint32_t (&r)[4], uint32_t a) {
  asm volatile("ldmatrix.sync.aligned.m8n8.x4.trans.shared.b16 {%0, %1, %2, %3}, [%4];"
               : "=r"(r[0]), "=r"(r[1]), "=r"(r[2]), "=r"(r[3]) : "r"(a) : "memory");
}
__device__ __forceinline__ uint32_t hfma2(uint32_t a, uint32_t b, uint32_t c) {
  uint32_t r; asm("fma.rn.bf16x2 %0, %1, %2, %3;" : "=r"(r) : "r"(a), "r"(b), "r"(c)); return r;
}
__device__ __forceinline__ void wait_cnt(int idx, unsigned target) {
  const unsigned* p = &g_cnt[idx * 32];
  int n = 0;
  while ((int)(ld_acq(p) - target) < 0) { if (timed_out(++n)) break; }
}
__device__ __forceinline__ void wait_all(const unsigned* p, unsigned target) {
  int n = 0;
  while (true) {
    const bool ok = (int)(ld_acq(p) - target) >= 0, to = timed_out(++n);
    if (__all_sync(0xffffffffu, ok | to)) break;
  }
}
constexpr unsigned FW = 1;
template <int NW> __device__ __forceinline__ void cta_flag(uint32_t cnt, unsigned* p) {
  unsigned old;
  asm volatile("atom.shared.inc.u32 %0, [%1], %2;" : "=r"(old) : "r"(cnt), "n"(NW - 1) : "memory");
  if (old == NW - 1) red_rlx(p);
}
__device__ __forceinline__ void fence_async_global() { asm volatile("fence.proxy.async.global;" ::: "memory"); }
__device__ __forceinline__ void fence_async_smem() { asm volatile("fence.proxy.async.shared::cta;" ::: "memory"); }
__device__ __forceinline__ void bar_sync(int id, int n) { asm volatile("bar.sync %0, %1;" ::"r"(id), "r"(n) : "memory"); }
__device__ __forceinline__ void bar_arrive(int id, int n) { asm volatile("bar.arrive %0, %1;" ::"r"(id), "r"(n) : "memory"); }
__device__ __forceinline__ void wg_fence() { asm volatile("wgmma.fence.sync.aligned;" ::: "memory"); }
__device__ __forceinline__ void wg_commit() { asm volatile("wgmma.commit_group.sync.aligned;" ::: "memory"); }
template <int N> __device__ __forceinline__ void wg_wait() { asm volatile("wgmma.wait_group.sync.aligned %0;" ::"n"(N) : "memory"); }
__device__ __forceinline__ uint64_t mkdesc(uint32_t addr, uint32_t lbo, uint32_t sbo) {
  return (uint64_t)((addr & 0x3FFFF) >> 4) | ((uint64_t)(lbo >> 4) << 16) | ((uint64_t)(sbo >> 4) << 32) | (1ull << 62);
}
__device__ __forceinline__ uint32_t desc_lo(uint32_t addr, uint32_t lbo) { return ((addr & 0x3FFFF) >> 4) | ((lbo >> 4) << 16); }
__device__ __forceinline__ uint64_t desc64(uint32_t lo) { return (uint64_t)lo | (0x40000040ull << 32); }
__device__ __forceinline__ uint32_t pack2(float lo, float hi) {
  uint32_t r; asm("cvt.rn.bf16x2.f32 %0, %1, %2;" : "=r"(r) : "f"(hi), "f"(lo)); return r;
}
__device__ __forceinline__ float lo_f(uint32_t v) { return __uint_as_float(v << 16); }
__device__ __forceinline__ float hi_f(uint32_t v) { return __uint_as_float(v & 0xffff0000u); }
__device__ __forceinline__ float ex2(float x) { float r; asm("ex2.approx.ftz.f32 %0, %1;" : "=f"(r) : "f"(x)); return r; }
__device__ __forceinline__ float rcp(float x) { float r; asm("rcp.approx.ftz.f32 %0, %1;" : "=f"(r) : "f"(x)); return r; }
__device__ __forceinline__ float tanh_a(float x) { float r; asm("tanh.approx.f32 %0, %1;" : "=f"(r) : "f"(x)); return r; }
__device__ __forceinline__ void sts128(uint32_t a, uint32_t x, uint32_t y, uint32_t z, uint32_t w) {
  asm volatile("st.shared.v4.b32 [%0], {%1, %2, %3, %4};" ::"r"(a), "r"(x), "r"(y), "r"(z), "r"(w) : "memory");
}
__device__ __forceinline__ float2 lds64f(uint32_t a) {
  float2 v; asm volatile("ld.shared.v2.f32 {%0, %1}, [%2];" : "=f"(v.x), "=f"(v.y) : "r"(a)); return v;
}
__device__ __forceinline__ void red_add2(float* p, float a, float b) {
  asm volatile("red.relaxed.gpu.global.add.v2.f32 [%0], {%1, %2};" ::"l"(p), "f"(a), "f"(b) : "memory");
}
__device__ __forceinline__ void mma16816(float (&c)[4], const uint32_t (&a)[4], uint32_t b0, uint32_t b1) {
  asm volatile("mma.sync.aligned.m16n8k16.row.col.f32.bf16.bf16.f32 {%0,%1,%2,%3}, {%4,%5,%6,%7}, {%8,%9}, {%0,%1,%2,%3};"
               : "+f"(c[0]), "+f"(c[1]), "+f"(c[2]), "+f"(c[3]) : "r"(a[0]), "r"(a[1]), "r"(a[2]), "r"(a[3]), "r"(b0), "r"(b1));
}
__device__ __forceinline__ float quad_sum(float v) {
  v += __shfl_xor_sync(0xffffffffu, v, 1);
  v += __shfl_xor_sync(0xffffffffu, v, 2);
  return v;
}
template<int TA, int TB> __device__ __forceinline__ void wgmma_ss_n64(float (&d)[32], uint64_t da, uint64_t db, int sd) {
  asm volatile("{\n.reg .pred p;\nsetp.ne.b32 p, %34, 0;\n"
    "wgmma.mma_async.sync.aligned.m64n64k16.f32.bf16.bf16 "
    "{%0, %1, %2, %3, %4, %5, %6, %7, %8, %9, %10, %11, %12, %13, %14, %15, %16, %17, %18, %19, %20, %21, %22, %23, %24, %25, %26, %27, %28, %29, %30, %31}, %32, %33, p, 1, 1, %35, %36;\n}\n"
    : "+f"(d[0]), "+f"(d[1]), "+f"(d[2]), "+f"(d[3]), "+f"(d[4]), "+f"(d[5]), "+f"(d[6]), "+f"(d[7]), "+f"(d[8]), "+f"(d[9]), "+f"(d[10]), "+f"(d[11]), "+f"(d[12]), "+f"(d[13]), "+f"(d[14]), "+f"(d[15]), "+f"(d[16]), "+f"(d[17]), "+f"(d[18]), "+f"(d[19]), "+f"(d[20]), "+f"(d[21]), "+f"(d[22]), "+f"(d[23]), "+f"(d[24]), "+f"(d[25]), "+f"(d[26]), "+f"(d[27]), "+f"(d[28]), "+f"(d[29]), "+f"(d[30]), "+f"(d[31])
    : "l"(da), "l"(db), "r"(sd), "n"(TA), "n"(TB));
}
template<int TA, int TB> __device__ __forceinline__ void wgmma_ss_n80(float (&d)[40], uint64_t da, uint64_t db, int sd) {
  asm volatile("{\n.reg .pred p;\nsetp.ne.b32 p, %42, 0;\n"
    "wgmma.mma_async.sync.aligned.m64n80k16.f32.bf16.bf16 "
    "{%0, %1, %2, %3, %4, %5, %6, %7, %8, %9, %10, %11, %12, %13, %14, %15, %16, %17, %18, %19, %20, %21, %22, %23, %24, %25, %26, %27, %28, %29, %30, %31, %32, %33, %34, %35, %36, %37, %38, %39}, %40, %41, p, 1, 1, %43, %44;\n}\n"
    : "+f"(d[0]), "+f"(d[1]), "+f"(d[2]), "+f"(d[3]), "+f"(d[4]), "+f"(d[5]), "+f"(d[6]), "+f"(d[7]), "+f"(d[8]), "+f"(d[9]), "+f"(d[10]), "+f"(d[11]), "+f"(d[12]), "+f"(d[13]), "+f"(d[14]), "+f"(d[15]), "+f"(d[16]), "+f"(d[17]), "+f"(d[18]), "+f"(d[19]), "+f"(d[20]), "+f"(d[21]), "+f"(d[22]), "+f"(d[23]), "+f"(d[24]), "+f"(d[25]), "+f"(d[26]), "+f"(d[27]), "+f"(d[28]), "+f"(d[29]), "+f"(d[30]), "+f"(d[31]), "+f"(d[32]), "+f"(d[33]), "+f"(d[34]), "+f"(d[35]), "+f"(d[36]), "+f"(d[37]), "+f"(d[38]), "+f"(d[39])
    : "l"(da), "l"(db), "r"(sd), "n"(TA), "n"(TB));
}
template<int TA, int TB> __device__ __forceinline__ void wgmma_ss_n160(float (&d)[80], uint64_t da, uint64_t db, int sd) {
  asm volatile("{\n.reg .pred p;\nsetp.ne.b32 p, %82, 0;\n"
    "wgmma.mma_async.sync.aligned.m64n160k16.f32.bf16.bf16 "
    "{%0, %1, %2, %3, %4, %5, %6, %7, %8, %9, %10, %11, %12, %13, %14, %15, %16, %17, %18, %19, %20, %21, %22, %23, %24, %25, %26, %27, %28, %29, %30, %31, %32, %33, %34, %35, %36, %37, %38, %39, %40, %41, %42, %43, %44, %45, %46, %47, %48, %49, %50, %51, %52, %53, %54, %55, %56, %57, %58, %59, %60, %61, %62, %63, %64, %65, %66, %67, %68, %69, %70, %71, %72, %73, %74, %75, %76, %77, %78, %79}, %80, %81, p, 1, 1, %83, %84;\n}\n"
    : "+f"(d[0]), "+f"(d[1]), "+f"(d[2]), "+f"(d[3]), "+f"(d[4]), "+f"(d[5]), "+f"(d[6]), "+f"(d[7]), "+f"(d[8]), "+f"(d[9]), "+f"(d[10]), "+f"(d[11]), "+f"(d[12]), "+f"(d[13]), "+f"(d[14]), "+f"(d[15]), "+f"(d[16]), "+f"(d[17]), "+f"(d[18]), "+f"(d[19]), "+f"(d[20]), "+f"(d[21]), "+f"(d[22]), "+f"(d[23]), "+f"(d[24]), "+f"(d[25]), "+f"(d[26]), "+f"(d[27]), "+f"(d[28]), "+f"(d[29]), "+f"(d[30]), "+f"(d[31]), "+f"(d[32]), "+f"(d[33]), "+f"(d[34]), "+f"(d[35]), "+f"(d[36]), "+f"(d[37]), "+f"(d[38]), "+f"(d[39]), "+f"(d[40]), "+f"(d[41]), "+f"(d[42]), "+f"(d[43]), "+f"(d[44]), "+f"(d[45]), "+f"(d[46]), "+f"(d[47]), "+f"(d[48]), "+f"(d[49]), "+f"(d[50]), "+f"(d[51]), "+f"(d[52]), "+f"(d[53]), "+f"(d[54]), "+f"(d[55]), "+f"(d[56]), "+f"(d[57]), "+f"(d[58]), "+f"(d[59]), "+f"(d[60]), "+f"(d[61]), "+f"(d[62]), "+f"(d[63]), "+f"(d[64]), "+f"(d[65]), "+f"(d[66]), "+f"(d[67]), "+f"(d[68]), "+f"(d[69]), "+f"(d[70]), "+f"(d[71]), "+f"(d[72]), "+f"(d[73]), "+f"(d[74]), "+f"(d[75]), "+f"(d[76]), "+f"(d[77]), "+f"(d[78]), "+f"(d[79])
    : "l"(da), "l"(db), "r"(sd), "n"(TA), "n"(TB));
}
template<int TB> __device__ __forceinline__ void wgmma_rs_n88(float (&d)[44], const uint32_t (&a)[4], uint64_t db, int sd) {
  asm volatile("{\n.reg .pred p;\nsetp.ne.b32 p, %49, 0;\n"
    "wgmma.mma_async.sync.aligned.m64n88k16.f32.bf16.bf16 "
    "{%0, %1, %2, %3, %4, %5, %6, %7, %8, %9, %10, %11, %12, %13, %14, %15, %16, %17, %18, %19, %20, %21, %22, %23, %24, %25, %26, %27, %28, %29, %30, %31, %32, %33, %34, %35, %36, %37, %38, %39, %40, %41, %42, %43}, {%44, %45, %46, %47}, %48, p, 1, 1, %50;\n}\n"
    : "+f"(d[0]), "+f"(d[1]), "+f"(d[2]), "+f"(d[3]), "+f"(d[4]), "+f"(d[5]), "+f"(d[6]), "+f"(d[7]), "+f"(d[8]), "+f"(d[9]), "+f"(d[10]), "+f"(d[11]), "+f"(d[12]), "+f"(d[13]), "+f"(d[14]), "+f"(d[15]), "+f"(d[16]), "+f"(d[17]), "+f"(d[18]), "+f"(d[19]), "+f"(d[20]), "+f"(d[21]), "+f"(d[22]), "+f"(d[23]), "+f"(d[24]), "+f"(d[25]), "+f"(d[26]), "+f"(d[27]), "+f"(d[28]), "+f"(d[29]), "+f"(d[30]), "+f"(d[31]), "+f"(d[32]), "+f"(d[33]), "+f"(d[34]), "+f"(d[35]), "+f"(d[36]), "+f"(d[37]), "+f"(d[38]), "+f"(d[39]), "+f"(d[40]), "+f"(d[41]), "+f"(d[42]), "+f"(d[43])
    : "r"(a[0]), "r"(a[1]), "r"(a[2]), "r"(a[3]), "l"(db), "r"(sd), "n"(TB));
}

template <int N> struct Pos {
  int slot = 0; uint32_t ph = 0;
  __device__ __forceinline__ Pos() {}
  __device__ __forceinline__ explicit Pos(int n) : slot(n % N), ph((n / N) & 1) {}
  __device__ __forceinline__ void next() { if (++slot == N) { slot = 0; ph ^= 1; } }
};

template <int N> __device__ __forceinline__ void zero(float (&a)[N]) {
#pragma unroll
  for (int i = 0; i < N; i++) a[i] = 0.f;
}

struct Params {
  const __nv_bfloat16 *x, *wphi, *w1, *b1, *w2, *b2;
};

#define P4KK 4
#define P1KK 4
#define P5KK 4
#define WO_SPLIT 2
#define WO_NS 100
#define W1_NS 0
#define BUB 1
#define FLK 16
#define P4ROW(kb) (((kb) & 15) * 128 + ((kb) >> 4) * 64)
#define QS 8
#define RSPL 0
#define TREE 0
#define FST 1
#define HST 1
#define TSL(i) do {} while (0)
#define XLATE 1
#define PUBK 0
#define XPF 5
#define OPP 7
constexpr int BAR_CONS = 1, BAR_SIG = 2, BAR_WG = 3, BAR_PP = 5;
#define PF_NS 700
constexpr float LOG2E = 1.4426950408889634f;

template <class F>
__device__ __forceinline__ float feature_map(const float (&t)[20], float rl, uint32_t (&o)[20], F tick) {
  float mx = t[0], mn = t[0];
#pragma unroll
  for (int i = 1; i < 20; i++) { mx = fmaxf(mx, t[i]); mn = fminf(mn, t[i]); }
  float bp = -mx * rl, bn = mn * rl;
  tick(0, bp);
  float ep[20], en[20];
  float sp = 0.f, sn = 0.f;
#pragma unroll
  for (int i = 0; i < 20; i++) {
    ep[i] = ex2(fmaf(t[i], rl, bp)); sp += ep[i];
    en[i] = ex2(fmaf(t[i], -rl, bn)); sn += en[i];
    if (i & 1) o[i >> 1] = pack2(ep[i - 1], ep[i]);
    if (i % 3 == 2) tick(1 + i / 3, sn);
  }
  float ra = sp * rcp(sn);
#pragma unroll
  for (int i = 0; i < 10; i++) o[10 + i] = pack2(en[2 * i] * ra, en[2 * i + 1] * ra);
  tick(7, ra);
  return sp;
}

__device__ __forceinline__ void ld_row20(const __nv_bfloat16* p, uint32_t (&v)[10]) {
#pragma unroll
  for (int i = 0; i < 5; i++) asm volatile("ld.global.nc.v2.b32 {%0, %1}, [%2];" : "=r"(v[2 * i]), "=r"(v[2 * i + 1]) : "l"(p + 4 * i));
}
__device__ __forceinline__ void sts_row20(uint32_t a, const uint32_t (&v)[10]) {
#pragma unroll
  for (int i = 0; i < 5; i++) sts64(a + i * 8, v[2 * i], v[2 * i + 1]);
}
__device__ __forceinline__ float2 sums20(const uint32_t (&v)[10]) {
  float s = 0.f, q = 0.f;
#pragma unroll
  for (int i = 0; i < 10; i++) { float a = lo_f(v[i]), b = hi_f(v[i]); s += a + b; q = fmaf(a, a, q); q = fmaf(b, b, q); }
  return make_float2(s, q);
}
template <int NW>
__device__ __forceinline__ void warp_store(const CUtensorMap* m, int c0, int c1, uint32_t src, int lane, uint32_t cnt, unsigned* flag) {
  fence_async_smem();
  __syncwarp();
  if (lane == 0) { tma_store2d(m, c0, c1, src); bulk_commit_wait(); cta_flag<NW>(cnt, flag); }
  __syncwarp();
}
__device__ __forceinline__ float2 ln2_coef(float s, float q) {
  float mean = s * (1.f / 640.f);
  float var = fmaxf(fmaf(-mean, mean, q * (1.f / 640.f)), 0.f);
  float ve = var + 1e-5f;
  float rr = rsqrtf(ve) * rsqrtf(var * rcp(ve) + 1e-5f);
  return make_float2(rr, -mean * rr);
}

__global__ void __launch_bounds__(NTHREADS, 1)
fused_kernel(const __grid_constant__ CUtensorMap tm_x, const __grid_constant__ CUtensorMap tm_act,
             const __grid_constant__ CUtensorMap tm_kv, const __grid_constant__ CUtensorMap tm_q,
             const __grid_constant__ CUtensorMap tm_u,
             const __grid_constant__ CUtensorMap tm_w1, const __grid_constant__ CUtensorMap tm_w2,
             const __grid_constant__ CUtensorMap ts_buf, const __grid_constant__ CUtensorMap ts_out,
             const __grid_constant__ CUtensorMap ts_u, const __grid_constant__ CUtensorMap tr_qkv,
             const __grid_constant__ CUtensorMap tr_wo, const __grid_constant__ CUtensorMap tm_h,
             const __grid_constant__ CUtensorMap ts_w, const Params prm) {
  extern __shared__ __align__(1024) uint8_t smem[];
  const uint32_t sb = smem_u32(smem);
  const int tid = threadIdx.x, warp = __shfl_sync(0xffffffffu, tid >> 5, 0), lane = tid & 31;
  const int c = blockIdx.x;
  const int mt = c >> 3, g = c & 7;
  const bool b1_on = (c & 15) < 15;
  const int dt = P4_DT(c), ft = P4_FT(c);
  auto FULL = [&](int i) { return sb + SM_BARS + 8 * i; };
  auto EMPTY = [&](int i) { return sb + SM_BARS + 8 * (B_EMPTY + i); };
  const int type = c >> 5, hh = c & 31;
  constexpr int P0_RAW = P1_STG + 26 * KB;

  if (tid == 288) {
    mbar_init(FULL(B_P0), 1);
    asm volatile("fence.mbarrier_init.release.cluster;" ::: "memory");
    mbar_expect(FULL(B_P0), 30720);
    const CUtensorMap* tr = type < 3 ? &tr_qkv : &tr_wo;
    const int col = ((type < 3 ? type * 640 : 0) + hh * 20) & ~7;
#pragma unroll
    for (int i = 0; i < 4; i++) tma2d(sb + P0_RAW + i * 7680, tr, col, i * 160, FULL(B_P0));
  }
  if (tid == 0) {
    *reinterpret_cast<volatile int*>(smem + SM_ABORT) = 0;
    *reinterpret_cast<volatile int*>(smem + SM_CNT) = 0;
    *reinterpret_cast<volatile int*>(smem + SM_CNT + 4) = 0;
    *reinterpret_cast<volatile int*>(smem + SM_CNT + 8) = 0;
    for (int i = 0; i < B_NRING; i++) { mbar_init(FULL(i), 1); mbar_init(EMPTY(i), i >= B_P3A && i < B_P3A + P3_NA ? 1 : 2); }
    mbar_init(FULL(B_MLDONE), 2);
    mbar_init(FULL(B_ODONE), 2);
    mbar_init(FULL(B_FLO), 1);
    mbar_init(FULL(B_FLH), 1);
    mbar_init(FULL(B_KVRDY), 1);
    mbar_init(FULL(B_STAT), 1);
    asm volatile("fence.mbarrier_init.release.cluster;" ::: "memory");
  }
  if (tid == 320) {
    prefetch_map(&ts_w); prefetch_map(&tm_x); prefetch_map(&ts_buf); prefetch_map(&tm_kv); prefetch_map(&tm_q); prefetch_map(&tm_act); prefetch_map(&tm_w1);
    prefetch_map(&ts_u); prefetch_map(&tm_u); prefetch_map(&tm_w2); prefetch_map(&ts_out); prefetch_map(&tm_h);
  }
  unsigned epoch;
  asm volatile("ld.relaxed.gpu.global.u32 %0, [%1];" : "=r"(epoch) : "l"(&g_epoch) : "memory");
  __syncthreads();
  const unsigned ep1 = epoch + 1;

  if (warp >= 8) {
    asm volatile("setmaxnreg.dec.sync.aligned.u32 40;");
    if (warp == 8) {
      uint32_t mlph = 0;
      for (int layer = 0; layer < 2; layer++) {
        {
          if (layer) { mbar_wait(FULL(B_MLDONE), mlph); mlph ^= 1; wait_all(&g_cnt[(C_X + mt) * 32], ep1 * 8 * FW); fence_async_global(); TS(58); }
          else mbar_wait(FULL(B_P0), 0);
          const CUtensorMap* tm = layer ? &tm_act : &tm_x;
          const int xrow = (layer ? R_X2 : 0) + mt * 128;
          Pos<P1_NA> r(layer * 15);
#pragma unroll 1
          for (int it = 0; it < 15; it++) {
            if (it == XPF && !layer && g < 5 && elect_one()) tma2d_prefetch(&tm_x, (5 + g) * 64, xrow);
            mbar_wait(EMPTY(B_P1A + r.slot), r.ph ^ 1);
            if (elect_one()) {
              mbar_expect(FULL(B_P1A + r.slot), 16384);
              tma2d(sb + P1_A + r.slot * 16384, tm, (it >= 10 ? it - 10 : it) * 64, xrow, FULL(B_P1A + r.slot));
            }
            r.next();
          }
        }
        {
          mbar_wait(FULL(B_MLDONE), mlph); mlph ^= 1;
          Pos<P3_NA> r(layer * 10);
#pragma unroll 1
          for (int it = 0; it < 10; it++) {
            if (it == 0) {
              wait_all(&g_cnt[(C_O + (layer * 16 + mt) * 2) * 32], ep1 * 8); fence_async_global();
              if (layer) TS(55);
              mbar_wait(FULL(B_ODONE), layer);
            }
            if (it == 5) { mbar_wait(FULL(B_FLO), layer); if (layer) TS(59); }
            mbar_wait(EMPTY(B_P3A + r.slot), r.ph ^ 1);
            if (elect_one()) {
              mbar_expect(FULL(B_P3A + r.slot), 16384);
              tma3d(sb + P3_A + r.slot * 16384, &tm_h, R_O + mt * 128 + (it >= 5 ? 64 : 0), it >= 5 ? 2 * it - 10 : 2 * it, FULL(B_P3A + r.slot));
            }
            r.next();
          }
          mbar_wait(FULL(B_MLDONE), mlph); mlph ^= 1;
        }
        if (b1_on) {
          Pos<P4_NA> r(layer * 8);
#pragma unroll 1
          for (int kb = 0; kb < 32; kb++) {
            if (kb == 0) { wait_all(&g_cnt[(C_H + layer * 2) * 32], ep1 * 128); fence_async_global(); if (layer) TS(56); }
            if (kb == FLK) mbar_wait(FULL(B_FLH), layer);
            mbar_wait(EMPTY(B_P4A + r.slot), r.ph ^ 1);
            if (elect_one()) {
              mbar_expect(FULL(B_P4A + r.slot), 16384);
              tma3d(sb + P4_A + r.slot * 16384, &tm_h, R_H + P4ROW(kb), dt * 2, FULL(B_P4A + r.slot));
            }
            r.next();
          }
          if (layer == 1 && c == 0 && lane == 0) g_epoch = ep1;
          mbar_wait(FULL(B_MLDONE), mlph); mlph ^= 1;
        }
        {
          wait_all(&g_cnt[(C_U + layer * 5 + ((80 * g + (lane & 1) * 79) >> 7)) * 32], ep1 * 24 * FW); fence_async_global();
          if (layer) TS(57);
          Pos<P5_NB> r(layer * 24);
#pragma unroll 1
          for (int kb = 0; kb < 24; kb++) {
            mbar_wait(EMPTY(B_P5B + r.slot), r.ph ^ 1);
            if (elect_one()) {
              mbar_expect(FULL(B_P5B + r.slot), 10240);
              tma5d(sb + P5_B + r.slot * 10240, &tm_u, kb * 64, g, FULL(B_P5B + r.slot));
            }
            r.next();
          }
        }
      }
    } else if (warp == 9) {
      uint32_t mlph = 0;
      for (int layer = 0; layer < 2; layer++) {
        if (!layer) { wait_all(&g_cnt[(C_W + g) * 32], ep1 * 8 * FW); fence_async_global(); TS(46); }
        {
          Pos<P1_NB> r(layer * 15);
#pragma unroll 1
          for (int it = 0; it < 15; it++) {
            if (layer) {
              if (it < 4) mbar_wait(EMPTY(B_P5A + ((0x5421 >> (4 * r.slot)) & 7)), 0);
              if (it == 4) { mbar_wait(FULL(B_MLDONE), mlph); mlph ^= 1; }
            } else if (it == 10) { wait_all(&g_cnt[(C_WO + g) * 32], ep1 * 8 * FW); fence_async_global(); }
            mbar_wait(EMPTY(B_P1B + r.slot), r.ph ^ 1);
            if (elect_one()) {
              mbar_expect(FULL(B_P1B + r.slot), 20480);
              if (it < 10) tma2d(sb + P1_B + r.slot * 20480, &tm_kv, it * 64, g * 240, FULL(B_P1B + r.slot));
              else tma3d(sb + P1_B + r.slot * 20480, &tm_q, g * 240 + 160, 2 * it - 20, FULL(B_P1B + r.slot));
            }
            r.next();
          }
        }
        mbar_wait(FULL(B_MLDONE), mlph); mlph ^= 1;
#pragma unroll 1
        for (int kb = 0; kb < 5; kb++) {
          if (kb == WO_SPLIT) mbar_wait(FULL(B_KVRDY), layer);
          if (elect_one()) {
            mbar_expect(FULL(B_P3B + kb), 20480);
            tma3d(sb + P3_B + kb * 20480, &tm_q, R_WO + g * 80, 2 * kb, FULL(B_P3B + kb));
          }
          __nanosleep(WO_NS);
        }
        if (b1_on) {
          Pos<P4_NB> r(layer * 32);
#pragma unroll 1
          for (int kb = 0; kb < 32; kb++) {
            if (kb < P4_NB) { mbar_wait(EMPTY(B_P3B + (8 * r.slot + 7) / 20), layer); if (W1_NS) __nanosleep(W1_NS); }
            mbar_wait(EMPTY(B_P4B + r.slot), r.ph ^ 1);
            if (elect_one()) {
              mbar_expect(FULL(B_P4B + r.slot), 8192);
              tma2d(sb + P4_B + r.slot * 8192, &tm_w1, ft * 64, P4ROW(kb), FULL(B_P4B + r.slot));
            }
            r.next();
          }
        }
        mbar_wait(FULL(B_MLDONE), mlph); mlph ^= 1;
        {
          Pos<P5_NA> r(layer * 8);
#pragma unroll 1
          for (int kb = 0; kb < 24; kb++) {
            mbar_wait(EMPTY(B_P5A + r.slot), r.ph ^ 1);
            if (elect_one()) {
              mbar_expect(FULL(B_P5A + r.slot), 16384);
              tma3d(sb + P5_A + r.slot * 16384, &tm_w2, kb * 64, mt * 2, FULL(B_P5A + r.slot));
            }
            r.next();
          }
        }
        if (b1_on) { mbar_wait(FULL(B_MLDONE), mlph); mlph ^= 1; }
      }
    } else {
      if (warp == 10) {
        bar_sync(BAR_SIG, 288);
        if (lane == 0) {
          red_rel(&g_cnt[C_P0 * 32]);
          wait_cnt(C_P0, ep1 * NCTA);
          mbar_arrive(FULL(B_STAT));
        }
      } else {
        mbar_wait(FULL(B_STAT), 0);
        if (lane == 0) {
          const char* p1 = reinterpret_cast<const char*>(prm.w1) + (size_t)c * 49152;
          const char* p2 = reinterpret_cast<const char*>(prm.w2) + (size_t)c * 49152;
#pragma unroll 1
          for (int i = 0; i < 16; i++) {
            l2_prefetch((i < 8 ? p1 : p2) + (i & 7) * 6144, 6144);
            __nanosleep(PF_NS);
          }
        }
      }
      __syncwarp();
      for (int layer = 0; layer < 2; layer++) {
        if (warp == 10) {
          float* src = &g_acc[Z_KV + (layer * 8 + g) * 3360];
          bar_sync(BAR_SIG, 288);
          if (lane == 0) {
            const bool sw = RSPL && (mt & 1);
            bulk_redadd(src + (sw ? 1680 : 0), sb + (sw ? SM_ST : P1_STG), 6720);
            bulk_redadd(src + (sw ? 0 : 1680), sb + (sw ? P1_STG : SM_ST), 6720);
            if (layer) TS(41);
            bulk_commit_wait();
            if (layer) TS(42);
            red_rlx(&g_cnt[(C_KV + layer * 8 + g) * 32]);
          }
          __syncwarp();
          wait_all(&g_cnt[(C_KV + layer * 8 + g) * 32], ep1 * 16);
          if (layer) TS(43);
          fence_async_global();
          if (lane == 0) {
            mbar_expect(FULL(B_KVRDY), 13440);
            bulk_load(sb + SM_ST, src, 13440, FULL(B_KVRDY));
          }
          mbar_wait(FULL(B_ODONE), layer);
          wait_all(&g_cnt[(C_O + (layer * 16 + mt) * 2 + 1) * 32], ep1 * 8);
          fence_async_global();
          if (lane == 0) mbar_arrive(FULL(B_FLO));
          if (b1_on) {
            mbar_wait(FULL(B_MLDONE), 1);
            wait_all(&g_cnt[(C_H + layer * 2 + 1) * 32], ep1 * 128);
            fence_async_global();
            if (lane == 0) mbar_arrive(FULL(B_FLH));
            if (layer) TS(60);
          }
        }
        __syncwarp();
      }
    }
  } else {
    asm volatile("setmaxnreg.inc.sync.aligned.u32 232;");
    const int wg = warp >> 2, wq = warp & 3, gq = lane >> 2, j = lane & 3;
    const bool elect = (tid & 127) == 0;
    const int lrow = wg * 64 + wq * 16 + gq;
    const int grow = mt * 128 + lrow;
    uint32_t xr[2][10];

    const uint32_t st_w = sb + SM_ST + warp * 2560;
    const uint32_t st_t = st_w + gq * 160 + j * 40;
    const unsigned tag = ep1 & 0xffu;
    uint2* const ll_b = &g_ll[(mt * 8 + warp) * 128];
    auto row_pub2 = [&](int ex, float2 u0, float2 u1) {
      float a = (j & 1) ? u0.x : u1.x, b = (j & 1) ? u0.y : u1.y;
      float s = ((j & 1) ? u1.x : u0.x) + __shfl_xor_sync(0xffffffffu, a, 1);
      float q = ((j & 1) ? u1.y : u0.y) + __shfl_xor_sync(0xffffffffu, b, 1);
      s += __shfl_xor_sync(0xffffffffu, s, 2); q += __shfl_xor_sync(0xffffffffu, q, 2);
      if (j < 2) st_ll(ll_b + ex * 16384 + g * 16 + gq * 2 + j, __float_as_uint(s), ((__float_as_uint(q) + 0x80u) & ~0xffu) | tag);
    };
    auto row_pub = [&](int ex) { row_pub2(ex, sums20(xr[0]), sums20(xr[1])); };
    uint4 lv[2];
    auto row_ld = [&](int ex) {
      const uint2* p = ll_b + ex * 16384 + j * 16 + gq * 2;
      lv[0] = ld_ll(p); lv[1] = ld_ll(p + 64);
    };
    auto row_get = [&](int ex, float2 (&st)[2]) {
      int n = 0;
      while (true) {
        const bool ok = (((lv[0].y ^ tag) | (lv[0].w ^ tag) | (lv[1].y ^ tag) | (lv[1].w ^ tag)) & 0xffu) == 0;
        const bool to = timed_out(++n);
        if (__all_sync(0xffffffffu, ok | to)) break;
        row_ld(ex);
      }
      st[0].x = quad_sum(__uint_as_float(lv[0].x) + __uint_as_float(lv[1].x));
      st[0].y = quad_sum(__uint_as_float(lv[0].y ^ tag) + __uint_as_float(lv[1].y ^ tag));
      st[1].x = quad_sum(__uint_as_float(lv[0].z) + __uint_as_float(lv[1].z));
      st[1].y = quad_sum(__uint_as_float(lv[0].w ^ tag) + __uint_as_float(lv[1].w ^ tag));
    };
    {
      const unsigned short* ph = reinterpret_cast<const unsigned short*>(prm.wphi) + hh * 400;
      auto aval = [&](int f, int d) -> uint32_t {
        if (f >= 20 || d >= 20) return 0u;
        if (type < 2) return (uint32_t)__ldg(ph + d * 20 + f);
        return f == d ? 0x3f80u : 0u;
      };
      auto apair = [&](int f, int d) -> uint32_t { return aval(f, d) | (aval(f, d + 1) << 16); };
      uint32_t a00[4] = {apair(gq, 2 * j), apair(gq + 8, 2 * j), apair(gq, 2 * j + 8), apair(gq + 8, 2 * j + 8)};
      uint32_t a01[4] = {apair(gq, 16 + 2 * j), apair(gq + 8, 16 + 2 * j), 0u, 0u};
      uint32_t a10[4] = {apair(16 + gq, 2 * j), 0u, apair(16 + gq, 2 * j + 8), 0u};
      uint32_t a11[4] = {apair(16 + gq, 16 + 2 * j), 0u, 0u, 0u};
      const uint32_t raw = sb + P0_RAW + (warp * 80 + gq) * 48 + (hh & 1) * 8 + j * 4;
      float cs0 = 0.f, cs1 = 0.f, cs2 = 0.f;
      float c0[10][4], c1[10][4];
      mbar_wait(FULL(B_P0), 0);
      TS(40);
#pragma unroll
      for (int t = 0; t < 10; t++) {
        uint32_t b0 = lds32(raw + t * 384), b1 = lds32(raw + t * 384 + 16), b2 = j < 2 ? lds32(raw + t * 384 + 32) : 0u;
        zero(c0[t]); zero(c1[t]);
        mma16816(c0[t], a00, b0, b1);
        mma16816(c0[t], a01, b2, 0u);
        mma16816(c1[t], a10, b0, b1);
        mma16816(c1[t], a11, b2, 0u);
        cs0 += c0[t][0] + c0[t][1]; cs1 += c0[t][2] + c0[t][3]; cs2 += c1[t][0] + c1[t][1];
      }
      cs0 = quad_sum(cs0); cs1 = quad_sum(cs1); cs2 = quad_sum(cs2);
      float* csm = reinterpret_cast<float*>(smem + SM_CS);
      if (j == 0) { csm[warp * 24 + gq] = cs0; csm[warp * 24 + 8 + gq] = cs1; csm[warp * 24 + 16 + gq] = cs2; }
      bar_sync(BAR_CONS, 256);
      cs0 = cs1 = cs2 = 0.f;
#pragma unroll
      for (int w = 0; w < 8; w++) { cs0 += csm[w * 24 + gq]; cs1 += csm[w * 24 + 8 + gq]; cs2 += csm[w * 24 + 16 + gq]; }
      const float msc = type < 3 ? -1.f / 640.f : 0.f;
      cs0 *= msc; cs1 *= msc; cs2 *= msc;
      const uint32_t s0 = sb + P1_STG + warp * 3200 + gq * 160 + j * 4;
#pragma unroll
      for (int t = 0; t < 10; t++) {
        sts32(s0 + t * 16, pack2(c0[t][0] + cs0, c0[t][1] + cs0));
        sts32(s0 + 1280 + t * 16, pack2(c0[t][2] + cs1, c0[t][3] + cs1));
        if (gq < 4) sts32(s0 + 2560 + t * 16, pack2(c1[t][0] + cs2, c1[t][1] + cs2));
      }
      fence_async_smem();
      __syncwarp();
      TS(44);
      if (lane == 0) {
        const int row8 = type < 3 ? (hh >> 2) * 30 + (type == 0 ? 20 : (type == 1 ? 0 : 10)) : R_WO / 8 + (hh >> 2) * 10;
        tma_store4d(&ts_w, ((type == 0 ? warp + 4 : warp) & 7) * 80, hh & 3, row8, sb + P1_STG + warp * 3200);
      }
      if (lane == 0) {
        bulk_commit_wait();
        cta_flag<8>(sb + SM_CNT, &g_cnt[((type == 1 || type == 2 ? C_W : C_WO) + (hh >> 2)) * 32]);
      }
      __syncwarp();
      TS(45);
      ld_row20(prm.x + (size_t)grow * 640 + g * 80 + j * 20, xr[0]);
      ld_row20(prm.x + (size_t)(grow + 8) * 640 + g * 80 + j * 20, xr[1]);
      st_ll(ll_b + (j < 2 ? 1 : 3) * 16384 + g * 16 + gq * 2 + (j & 1), 0u, tag ^ 1u);
      row_pub(0);
      if (tid < 105) reinterpret_cast<float4*>(g_acc)[c * 105 + tid] = make_float4(0.f, 0.f, 0.f, 0.f);
      bar_arrive(BAR_SIG, 288);
      TS(1);
    }

    for (int layer = 0; layer < 2; layer++) {
      uint32_t phq[2][20];
      float qeps[2];
      {
        Pos<P1_NA> r1a(layer * 15); Pos<P1_NB> r1b(layer * 15);
        float kvacc[80]; zero(kvacc);
        int pb = 0;
        auto kv_steps = [&](int k0, int k1) {
#pragma unroll 1
          for (int kb = k0; kb < k1; kb++) {
            mbar_wait(FULL(B_P1A + r1a.slot), r1a.ph);
            mbar_wait(FULL(B_P1B + r1b.slot), r1b.ph);
            uint64_t da = mkdesc(sb + P1_A + r1a.slot * 16384 + wg * 8192, 16, 1024);
            uint64_t db = mkdesc(sb + P1_B + r1b.slot * 20480, 16, 1024);
            wg_fence();
#pragma unroll
            for (int kk = 0; kk < P1KK; kk++) wgmma_ss_n160<0, 0>(kvacc, da + kk * 2, db + kk * 2, (kb | kk) != 0);
            wg_commit();
            if (kb == 0) TSL(2 + layer * 16);
            if (kb) {
              wg_wait<1>();
              if (elect) {
                if (kb <= 5) mbar_arrive(EMPTY(B_P1A + kb - 1));
                mbar_arrive(EMPTY(B_P1B + pb));
              }
            }
            pb = r1b.slot;
            r1a.next(); r1b.next();
          }
        };
        kv_steps(PUBK, 7);
        row_ld(2 * layer);
        kv_steps(7, 10);
        float qacc[40]; zero(qacc);
        auto q_release = [&](int i0, int i1) {
          if (elect) {
#pragma unroll
            for (int i = i0; i < i1; i++) {
              mbar_arrive(EMPTY(B_P1A + i % 5));
              if (i & 1) mbar_arrive(EMPTY(B_P1B + Pos<P1_NB>(layer * 15 + 10 + (i >> 1)).slot));
            }
          }
        };
        float rl[2];
        {
          float2 st[2];
          row_get(2 * layer, st);
#pragma unroll
          for (int r = 0; r < 2; r++) {
            float mean = st[r].x * (1.f / 640.f);
            rl[r] = rsqrtf(fmaxf(fmaf(-mean, mean, st[r].y * (1.f / 640.f)), 0.f) + 1e-5f);
          }
        }
        wg_wait<0>();
        if (elect) mbar_arrive(EMPTY(B_P1B + pb));
        TS(3 + layer * 16);
        uint64_t qa = mkdesc(sb + P1_A + wg * 8192, 16, 1024), qb = 0;
        auto q_tick = [&](int n) {
          if ((n & 7) == 0) {
            const Pos<P1_NB> p(layer * 15 + 10 + (n >> 3));
            mbar_wait(FULL(B_P1B + p.slot), p.ph);
            qb = mkdesc(sb + P1_B + p.slot * 20480, 16, 1024);
            wg_fence();
          }
          if (n == 12) { wg_wait<1>(); q_release(0, 2); }
          wgmma_ss_n80<0, 0>(qacc, qa, qb, n != 0);
          qa += (n & 3) == 3 ? 1024 - 6 : 2;
          qb += (n & 3) == 3 ? 640 - 6 : 2;
          if (n == 7 || n == 11 || n == 19) wg_commit();
        };
        const uint32_t anchor = sb + SM_CS + lane * 4;
        const int sub = j & 1;
        const uint32_t sw = gq ^ (j & 2);
        const uint32_t stg = sb + P1_STG + (j >> 1) * 32768 + (lrow - gq + sw) * 128;
#pragma unroll
        for (int r = 0; r < 2; r++) {
          float t[20];
#pragma unroll
          for (int i = 0; i < 10; i++) { t[2 * i] = kvacc[i * 4 + 2 * r]; t[2 * i + 1] = kvacc[i * 4 + 2 * r + 1]; }
          uint32_t ph[20];
          const float ip = rcp(feature_map(t, rl[r] * LOG2E, ph, [&](int k, float v) { sts32(anchor, __float_as_uint(v)); q_tick(10 * r + k); }));
          const uint32_t rb0 = stg + r * 1024, ab = rb0 + 16384;
#pragma unroll
          for (int ch = 0; ch < 4; ch++) {
            int cidx = 5 * sub + ch;
            uint32_t addr = cidx < 8 ? rb0 + ((cidx ^ sw) << 4) : ab + (((cidx - 2) ^ sw) << 4);
            sts128(addr, ph[4 * ch], ph[4 * ch + 1], ph[4 * ch + 2], ph[4 * ch + 3]);
          }
          q_tick(10 * r + 8);
          const float vs = rl[r] * ip;
          uint32_t vv[10];
#pragma unroll
          for (int i = 0; i < 10; i++) vv[i] = pack2(kvacc[40 + i * 4 + 2 * r] * vs, kvacc[40 + i * 4 + 2 * r + 1] * vs);
          sts128(sub ? ab + ((3 ^ sw) << 4) : rb0 + ((4 ^ sw) << 4), sub ? vv[0] : ph[16], sub ? vv[1] : ph[17], sub ? vv[2] : ph[18], sub ? vv[3] : ph[19]);
          sts128(sub ? ab + ((7 ^ sw) << 4) : ab + (sw << 4), sub ? ph[16] : vv[0], sub ? ph[17] : vv[1], sub ? ph[18] : vv[2], sub ? ph[19] : vv[3]);
          sts128(ab + (((3 * sub + 1) ^ sw) << 4), vv[4], vv[5], vv[6], vv[7]);
          sts128(ab + (((3 * sub + 2) ^ sw) << 4), vv[8], vv[9], pack2(ip, 0.f), 0u);
          q_tick(10 * r + 9);
        }
        fence_async_smem();
        bar_sync(BAR_CONS, 256);
        TS(4 + layer * 16);
        {
          float dacc[40]; zero(dacc);
          const uint32_t pt = sb + P1_STG + wg * 32768;
          uint64_t da = mkdesc(pt + 16384, 16384, 1024);
          uint64_t db = mkdesc(pt, 16384 + 96, 1024);
          wg_fence();
#pragma unroll
          for (int kk = 0; kk < 8; kk++) wgmma_ss_n80<1, 1>(dacc, da + kk * 128, db + kk * 128, kk != 0);
          wg_commit();
          wg_wait<1>(); q_release(2, 5);
          wg_wait<0>();
          bar_sync(BAR_WG + wg, 128);
#pragma unroll
          for (int r = 0; r < 2; r++) {
            int rho = wq * 16 + gq + 8 * r;
            int sr = rho >= 24, dd = rho - 24 * sr;
            if (dd <= 20) {
              uint32_t dst = sb + (wg ? SM_ST : P1_STG) + (sr * 21 + dd) * 160 + 8 * j;
#pragma unroll
              for (int ii = 0; ii < 5; ii++) {
                float v0 = sr ? dacc[(5 + ii) * 4 + 2 * r] : dacc[ii * 4 + 2 * r];
                float v1 = sr ? dacc[(5 + ii) * 4 + 2 * r + 1] : dacc[ii * 4 + 2 * r + 1];
                sts64(dst + ii * 32, __float_as_uint(v0), __float_as_uint(v1));
              }
            }
          }
          fence_async_smem();
          bar_arrive(BAR_SIG, 288);
          TS(5 + layer * 16);
        }
        {
          const uint32_t zb = sb + (wg ? P1_STG + 32768 : P2_B) + (tid & 127) * 16, ze = sb + (wg ? P2_B + 33792 : P1_STG + 32768);
          const Pos<P1_NB> p12(layer * 15 + 12), p13(layer * 15 + 13), p14(layer * 15 + 14);
          const uint64_t d12 = mkdesc(sb + P1_B + p12.slot * 20480, 16, 1024), d13 = mkdesc(sb + P1_B + p13.slot * 20480, 16, 1024),
                         d14 = mkdesc(sb + P1_B + p14.slot * 20480, 16, 1024);
          mbar_wait(FULL(B_P1B + p13.slot), p13.ph);
          mbar_wait(FULL(B_P1B + p14.slot), p14.ph);
          bool ok = false;
          if (wg) bar_sync(BAR_PP + 2, 256);
#pragma unroll
          for (int i = 5; i < 10; i++) {
            if (!ok) mbar_wait(FULL(B_P1A + i - 5), r1a.ph);
            const uint64_t da = mkdesc(sb + P1_A + (i - 5) * 16384 + wg * 8192, 16, 1024);
            const uint64_t db = (i < 6 ? d12 : (i < 8 ? d13 : d14)) + (i & 1) * 640;
            wg_fence();
            wgmma_ss_n80<0, 0>(qacc, da, db, 1);
            wgmma_ss_n80<0, 0>(qacc, da + 2, db + 2, 1);
            if (i < 9) ok = mbar_test(FULL(B_P1A + i - 4), r1a.ph);
#pragma unroll
            for (int u = 0; u < 3; u++) {
              const uint32_t za = zb + ((i - 5) * 3 + u) * 2048;
              if ((i - 5) * 3 + u < 11 && za < ze) sts128(za, 0u, 0u, 0u, 0u);
            }
            if (i == QS && !wg) bar_arrive(BAR_PP + 2, 256);
            wgmma_ss_n80<0, 0>(qacc, da + 4, db + 4, 1);
            wgmma_ss_n80<0, 0>(qacc, da + 6, db + 6, 1);
          }
          wg_commit();
        }
        wg_wait<0>(); q_release(5, 10);
        if (elect) mbar_arrive(FULL(B_MLDONE));
        TS(6 + layer * 16);
        if (layer) TSB(83);
#pragma unroll
        for (int r = 0; r < 2; r++) {
          float t[20];
#pragma unroll
          for (int i = 0; i < 10; i++) { t[2 * i] = qacc[i * 4 + 2 * r]; t[2 * i + 1] = qacc[i * 4 + 2 * r + 1]; }
          qeps[r] = 1e-6f * feature_map(t, rl[r] * LOG2E, phq[r], [](int, float) {});
        }
      }
      {
        uint32_t ksrc[4], kdst[4];
#pragma unroll
        for (int it = 0; it < 4; it++) {
          int idx = min(tid + 256 * it, 839);
          int rowi = idx / 10, q4 = idx - rowi * 10;
          int hj = rowi / 21, dim = rowi - hj * 21;
          int n = dim < 20 ? 8 * (dim >> 1) + 2 * hj + (dim & 1) : 80 + 2 * hj;
          int ch = 2 * q4;
          ksrc[it] = sb + SM_ST + idx * 16;
          kdst[it] = sb + P2_B + (ch >> 3) * 11264 + n * 128 + hj * 4 + (((ch & 7) ^ (n & 7)) << 4);
        }
        if (layer) { TS(84); TSB(85); }
        bar_sync(BAR_CONS, 256);
        TS(7 + layer * 16);
        mbar_wait(FULL(B_KVRDY), layer);
        TS(8 + layer * 16);
        float4 kvv[4];
#pragma unroll
        for (int it = 0; it < 4; it++) {
          kvv[it] = lds128f(ksrc[it]);

        }
#pragma unroll
        for (int it = 0; it < 4; it++) {
          sts32(kdst[it], pack2(kvv[it].x, kvv[it].y));
          sts32(kdst[it] ^ 16, pack2(kvv[it].z, kvv[it].w));
        }
        fence_async_smem();
        if (layer) TS(50);
        bar_sync(BAR_CONS, 256);
        float oacc[44]; zero(oacc);
        if (wg) bar_sync(BAR_PP, 256);
        wg_fence();
#pragma unroll
        for (int t = 0; t < 10; t++) {
          uint32_t a[4] = {phq[0][2 * t], phq[1][2 * t], phq[0][2 * t + 1], phq[1][2 * t + 1]};
          uint64_t db = mkdesc(sb + P2_B + (t >> 2) * 11264 + (t & 3) * 32, 16, 1024);
          wgmma_rs_n88<0>(oacc, a, db, t != 0);
          if (t == OPP && !wg) bar_arrive(BAR_PP, 256);
        }
        wg_commit();
        wg_wait<0>();
        if (elect) mbar_arrive(FULL(B_ODONE));
        if (layer) { TS(51); TSB(53); }
#pragma unroll
        for (int r = 0; r < 2; r++) {
          float inv = rcp(oacc[40 + 2 * r] + qeps[r]);
          uint32_t ov[10];
#pragma unroll
          for (int i = 0; i < 10; i++) ov[i] = pack2(oacc[i * 4 + 2 * r] * inv, oacc[i * 4 + 2 * r + 1] * inv);
          sts_row20(st_t + r * 1280, ov);
        }
        warp_store<4>(&ts_buf, g * 80, R_O + mt * 128 + warp * 16, st_w, lane, sb + SM_CNT + 4 + 4 * wg, &g_cnt[(C_O + (layer * 16 + mt) * 2 + wg) * 32]);
        TS(9 + layer * 16);
        if (layer) TSB(34);
      }
      uint32_t bias[8];
#pragma unroll
      for (int i = 0; i < 8; i++) bias[i] = __ldg(reinterpret_cast<const uint32_t*>(prm.b1 + (b1_on ? ft : 0) * 64 + i * 8) + j);
      float b2v[2];
      b2v[0] = __bfloat162float(prm.b2[grow]); b2v[1] = __bfloat162float(prm.b2[grow + 8]);
      {
        float acc[40];
#pragma unroll
        for (int i = 0; i < 20; i++) { acc[2 * i] = lo_f(xr[i & 1][i >> 1]); acc[2 * i + 1] = hi_f(xr[i & 1][i >> 1]); }
        Pos<P3_NA> r3a(layer * 10 + wg * 5);
        int pa = 0;
        bool oka = false;
#pragma unroll
        for (int i = 0; i < 5; i++) mbar_wait(FULL(B_P3B + i), layer);
        if (wg) bar_sync(BAR_PP + 1, 256);
#pragma unroll 1
        for (int kb = 0; kb < 5; kb++) {
          if (!oka) mbar_wait(FULL(B_P3A + r3a.slot), r3a.ph);
          uint64_t da = mkdesc(sb + P3_A + r3a.slot * 16384, 16, 1024);
          uint64_t db = mkdesc(sb + P3_B + kb * 20480, 16, 1024);
          const int ca = r3a.slot;
          r3a.next();
          wg_fence();
          wgmma_ss_n80<0, 0>(acc, da, db, 1);
          wgmma_ss_n80<0, 0>(acc, da + 2, db + 2, 1);
          wgmma_ss_n80<0, 0>(acc, da + 4, db + 4, 1);
          wgmma_ss_n80<0, 0>(acc, da + 6, db + 6, 1);
          oka = mbar_test(FULL(B_P3A + r3a.slot), r3a.ph);
          wgmma_ss_n80<0, 0>(acc, da + 512, db + 640, 1);
          wgmma_ss_n80<0, 0>(acc, da + 514, db + 642, 1);
          if (kb == 4 && !wg) bar_arrive(BAR_PP + 1, 256);
          wgmma_ss_n80<0, 0>(acc, da + 516, db + 644, 1);
          wgmma_ss_n80<0, 0>(acc, da + 518, db + 646, 1);
          wg_commit();
          if (wg) wg_wait<0>();
          if (kb) { wg_wait<1>(); if (elect) { mbar_arrive(EMPTY(B_P3A + pa)); mbar_arrive(EMPTY(B_P3B + kb - 1)); } } else { TSL(10 + layer * 16); }
          pa = ca;
        }
        wg_wait<0>();
        if (elect) { mbar_arrive(EMPTY(B_P3A + pa)); mbar_arrive(FULL(B_MLDONE)); }
        if (layer) TSB(36);
        TS(11 + layer * 16);
        {
          float2 us[2];
#pragma unroll
          for (int r = 0; r < 2; r++) {
            float s0 = 0.f, s1 = 0.f, q0 = 0.f, q1 = 0.f;
#pragma unroll
            for (int i = 0; i < 10; i++) {
              const float a = acc[i * 4 + 2 * r], b = acc[i * 4 + 2 * r + 1];
              s0 += a; s1 += b; q0 = fmaf(a, a, q0); q1 = fmaf(b, b, q1);
            }
            us[r] = make_float2(s0 + s1, q0 + q1);
          }
          row_pub2(2 * layer + 1, us[0], us[1]);
          if (layer) { TS(47); TSB(38); }
          row_ld(2 * layer + 1);
#pragma unroll
          for (int r = 0; r < 2; r++)
#pragma unroll
            for (int i = 0; i < 10; i++) {
              xr[r][i] = pack2(acc[i * 4 + 2 * r], acc[i * 4 + 2 * r + 1]);
              acc[i * 4 + 2 * r] = lo_f(xr[r][i]); acc[i * 4 + 2 * r + 1] = hi_f(xr[r][i]);
              asm volatile("" : "+f"(acc[i * 4 + 2 * r]), "+f"(acc[i * 4 + 2 * r + 1]));
            }
          float2 st[2];
          row_get(2 * layer + 1, st);
          if (layer) { TS(48); TSB(39); }
#pragma unroll
          for (int r = 0; r < 2; r++) {
            float2 k = ln2_coef(st[r].x, st[r].y);
            uint32_t hv[10];
#pragma unroll
            for (int i = 0; i < 10; i++) hv[i] = pack2(fmaf(acc[i * 4 + 2 * r], k.x, k.y), fmaf(acc[i * 4 + 2 * r + 1], k.x, k.y));
            sts_row20(st_t + r * 1280, hv);
          }
          if (layer) { TS(49); TSB(52); }
          warp_store<4>(&ts_buf, g * 80, R_H + mt * 128 + warp * 16, st_w, lane, sb + SM_CNT + 4 + 4 * wg, &g_cnt[(C_H + layer * 2 + wg) * 32]);
          if (layer) TSB(37);
        }
        TS(12 + layer * 16);
      }
      if (b1_on) {
        float acc[32];
#pragma unroll
        for (int i = 0; i < 16; i++) { acc[2 * i] = lo_f(bias[i >> 1]); acc[2 * i + 1] = hi_f(bias[i >> 1]); }
        Pos<P4_NA> r4a(layer * 8); Pos<P4_NB> r4b(layer * 32);
        int pa = 0, pb = 0;
        bool oka = false, okb = false;
#pragma unroll 1
        for (int kb = 0; kb < 32; kb++) {
          if (!oka) mbar_wait(FULL(B_P4A + r4a.slot), r4a.ph);
          if (!okb) mbar_wait(FULL(B_P4B + r4b.slot), r4b.ph);
          uint64_t da = mkdesc(sb + P4_A + r4a.slot * 16384 + wg * 8192, 8192, 1024);
          uint64_t db = mkdesc(sb + P4_B + r4b.slot * 8192, 8192, 1024);
          const int ca = r4a.slot, cb = r4b.slot;
          r4a.next(); r4b.next();
          wg_fence();
          wgmma_ss_n64<1, 1>(acc, da, db, 1);
          wgmma_ss_n64<1, 1>(acc, da + 128, db + 128, 1);
          oka = mbar_test(FULL(B_P4A + r4a.slot), r4a.ph);
          okb = mbar_test(FULL(B_P4B + r4b.slot), r4b.ph);
          wgmma_ss_n64<1, 1>(acc, da + 256, db + 256, 1);
          wgmma_ss_n64<1, 1>(acc, da + 384, db + 384, 1);
          wg_commit();
          if (kb) { wg_wait<1>(); if (elect) { mbar_arrive(EMPTY(B_P4A + pa)); mbar_arrive(EMPTY(B_P4B + pb)); } } else TSL(13 + layer * 16);
          pa = ca; pb = cb;
        }
        wg_wait<0>();
        if (elect) { mbar_arrive(EMPTY(B_P4A + pa)); mbar_arrive(EMPTY(B_P4B + pb)); mbar_arrive(FULL(B_MLDONE)); }
        TS(14 + layer * 16);
        if (layer) TSB(80);
#pragma unroll
        for (int r = 0; r < 2; r++) {
          const uint32_t dst = sb + SM_ST + warp * 2048 + (gq + 8 * r) * 128 + j * 4;
#pragma unroll
          for (int i = 0; i < 8; i++) {
            float v0 = acc[i * 4 + 2 * r], v1 = acc[i * 4 + 2 * r + 1];
            float t0 = tanh_a(v0 * fmaf(v0 * v0, 0.0356774081f, 0.7978845608f));
            float t1 = tanh_a(v1 * fmaf(v1 * v1, 0.0356774081f, 0.7978845608f));
            float h0 = 0.5f * v0, h1 = 0.5f * v1;
            sts32(dst + ((i ^ gq) << 4), pack2(fmaf(h0, t0, h0), fmaf(h1, t1, h1)));
          }
        }
        warp_store<8>(&ts_u, ft * 64, dt * 128 + warp * 16, sb + SM_ST + warp * 2048, lane, sb + SM_CNT, &g_cnt[(C_U + layer * 5 + dt) * 32]);
        if (layer) { TS(54); TSB(82); }
      }
      {
        float acc[40];
#pragma unroll
        for (int i = 0; i < 20; i++) { acc[2 * i] = lo_f(xr[i & 1][i >> 1]) + b2v[i & 1]; acc[2 * i + 1] = hi_f(xr[i & 1][i >> 1]) + b2v[i & 1]; }
        Pos<P5_NA> r5a(layer * 8); Pos<P5_NB> r5b(layer * 24);
        int pa = 0, pb = 0;
        bool oka = false, okb = false;
#pragma unroll 1
        for (int kb = 0; kb < 24; kb++) {
          if (!oka) mbar_wait(FULL(B_P5A + r5a.slot), r5a.ph);
          if (!okb) mbar_wait(FULL(B_P5B + r5b.slot), r5b.ph);
          uint64_t da = mkdesc(sb + P5_A + r5a.slot * 16384 + wg * 8192, 8192, 1024);
          uint64_t db = mkdesc(sb + P5_B + r5b.slot * 10240, 16, 1024);
          const int ca = r5a.slot, cb = r5b.slot;
          r5a.next(); r5b.next();
          wg_fence();
          wgmma_ss_n80<1, 0>(acc, da, db, 1);
          wgmma_ss_n80<1, 0>(acc, da + 128, db + 2, 1);
          oka = mbar_test(FULL(B_P5A + r5a.slot), r5a.ph);
          okb = mbar_test(FULL(B_P5B + r5b.slot), r5b.ph);
          wgmma_ss_n80<1, 0>(acc, da + 256, db + 4, 1);
          wgmma_ss_n80<1, 0>(acc, da + 384, db + 6, 1);
          wg_commit();
          if (kb) { wg_wait<1>(); if (elect) { mbar_arrive(EMPTY(B_P5A + pa)); mbar_arrive(EMPTY(B_P5B + pb)); } } else TSL(15 + layer * 16);
          pa = ca; pb = cb;
        }
        wg_wait<0>();
        if (elect) { mbar_arrive(EMPTY(B_P5A + pa)); mbar_arrive(EMPTY(B_P5B + pb)); mbar_arrive(FULL(B_MLDONE)); }
        TS(16 + layer * 16);
        if (!layer) TSB(81);
#pragma unroll
        for (int r = 0; r < 2; r++) {
#pragma unroll
          for (int i = 0; i < 10; i++)
            xr[r][i] = pack2(acc[i * 4 + 2 * r], acc[i * 4 + 2 * r + 1]);
          sts_row20(st_t + r * 1280, xr[r]);
        }
        fence_async_smem();
        __syncwarp();
        if (lane == 0) tma_store2d(layer ? &ts_out : &ts_buf, g * 80, (layer ? 0 : R_X2) + mt * 128 + warp * 16, st_w);
        if (!layer) row_pub(2);
        if (lane == 0) {
          bulk_commit_wait();
          if (!layer) cta_flag<8>(sb + SM_CNT, &g_cnt[(C_X + mt) * 32]);
        }
        __syncwarp();
        TS(17 + layer * 16);
      }
    }
  }
}

typedef CUresult (*EncodeFn)(CUtensorMap*, CUtensorMapDataType, cuuint32_t, void*, const cuuint64_t*, const cuuint64_t*,
                             const cuuint32_t*, const cuuint32_t*, CUtensorMapInterleave, CUtensorMapSwizzle,
                             CUtensorMapL2promotion, CUtensorMapFloatOOBfill);

void make_map(EncodeFn fn, CUtensorMap* m, const void* base, uint64_t cols, uint64_t rows, uint32_t box_cols, uint32_t box_rows, bool swz) {
  cuuint64_t dims[2] = {cols, rows};
  cuuint64_t strides[1] = {cols * 2};
  cuuint32_t box[2] = {box_cols, box_rows};
  cuuint32_t es[2] = {1, 1};
  fn(m, CU_TENSOR_MAP_DATA_TYPE_BFLOAT16, 2, const_cast<void*>(base), dims, strides, box, es, CU_TENSOR_MAP_INTERLEAVE_NONE,
     swz ? CU_TENSOR_MAP_SWIZZLE_128B : CU_TENSOR_MAP_SWIZZLE_NONE, CU_TENSOR_MAP_L2_PROMOTION_L2_256B, CU_TENSOR_MAP_FLOAT_OOB_FILL_NONE);
}

void make_map3(EncodeFn fn, CUtensorMap* m, const void* base, uint64_t cols, uint64_t rows, uint32_t box_rows) {
  cuuint64_t dims[3] = {64, rows, cols / 64};
  cuuint64_t strides[2] = {cols * 2, 128};
  cuuint32_t box[3] = {64, box_rows, 2};
  cuuint32_t es[3] = {1, 1, 1};
  fn(m, CU_TENSOR_MAP_DATA_TYPE_BFLOAT16, 3, const_cast<void*>(base), dims, strides, box, es, CU_TENSOR_MAP_INTERLEAVE_NONE,
     CU_TENSOR_MAP_SWIZZLE_128B, CU_TENSOR_MAP_L2_PROMOTION_L2_256B, CU_TENSOR_MAP_FLOAT_OOB_FILL_NONE);
}

}

extern "C" void kernel_launch(void* const* d_in, const int* in_sizes, int n_in, void* d_out, int out_size) {
  static bool init = false;
  static CUtensorMap tm_x, tm_act, tm_kv, tm_q, tm_u, tm_w1, tm_w2, ts_buf, ts_out, ts_u, tr_qkv, tr_wo, tm_h, ts_w;
  static const void* cached[6] = {nullptr, nullptr, nullptr, nullptr, nullptr, nullptr};
  if (!init || cached[0] != d_in[0] || cached[1] != d_in[5] || cached[2] != d_in[7] || cached[3] != d_out || cached[4] != d_in[1] ||
      cached[5] != d_in[3]) {
    void* fnp = nullptr;
    cudaDriverEntryPointQueryResult qr;
    cudaGetDriverEntryPoint("cuTensorMapEncodeTiled", &fnp, cudaEnableDefault, &qr);
    EncodeFn fn = (EncodeFn)fnp;
    void *p_buf, *p_u;
    cudaGetSymbolAddress(&p_buf, g_buf);
    cudaGetSymbolAddress(&p_u, g_u);
    make_map(fn, &tm_x, d_in[0], 640, 2048, 64, 128, true);
    make_map(fn, &tm_act, p_buf, 640, R_END, 64, 128, true);
    make_map3(fn, &tm_h, p_buf, 640, R_END, 64);
    make_map(fn, &tm_kv, p_buf, 640, R_END, 64, 160, true);
    make_map3(fn, &tm_q, p_buf, 640, R_END, 80);
    make_map(fn, &tm_w1, d_in[5], 1536, 2048, 64, 64, true);
    make_map3(fn, &tm_w2, d_in[7], 2048, 1536, 64);
    make_map(fn, &ts_buf, p_buf, 640, R_END, 80, 16, false);
    make_map(fn, &ts_out, d_out, 640, 2048, 80, 16, false);
    make_map(fn, &ts_u, p_u, 1536, 640, 64, 16, true);
    make_map(fn, &tr_qkv, d_in[1], 1920, 640, 24, 160, false);
    make_map(fn, &tr_wo, d_in[3], 640, 640, 24, 160, false);
    {
      cuuint64_t dims[5] = {1536, 2, 4, 10, 8};
      cuuint64_t strides[4] = {3072, 20 * 3072, 2 * 3072, 80 * 3072};
      cuuint32_t box[5] = {64, 2, 4, 10, 1};
      cuuint32_t es[5] = {1, 1, 1, 1, 1};
      fn(&tm_u, CU_TENSOR_MAP_DATA_TYPE_BFLOAT16, 5, p_u, dims, strides, box, es, CU_TENSOR_MAP_INTERLEAVE_NONE,
         CU_TENSOR_MAP_SWIZZLE_128B, CU_TENSOR_MAP_L2_PROMOTION_L2_256B, CU_TENSOR_MAP_FLOAT_OOB_FILL_NONE);
    }
    {
      cuuint64_t dims[4] = {640, 2, 4, R_X2 / 8};
      cuuint64_t strides[3] = {1280, 2 * 1280, 8 * 1280};
      cuuint32_t box[4] = {80, 2, 1, 10};
      cuuint32_t es[4] = {1, 1, 1, 1};
      fn(&ts_w, CU_TENSOR_MAP_DATA_TYPE_BFLOAT16, 4, p_buf, dims, strides, box, es, CU_TENSOR_MAP_INTERLEAVE_NONE,
         CU_TENSOR_MAP_SWIZZLE_NONE, CU_TENSOR_MAP_L2_PROMOTION_L2_256B, CU_TENSOR_MAP_FLOAT_OOB_FILL_NONE);
    }
    cudaFuncSetAttribute(fused_kernel, cudaFuncAttributeMaxDynamicSharedMemorySize, SM_TOTAL);
    cached[0] = d_in[0]; cached[1] = d_in[5]; cached[2] = d_in[7]; cached[3] = d_out; cached[4] = d_in[1]; cached[5] = d_in[3];
    init = true;
  }
  Params p;
  p.x = (const __nv_bfloat16*)d_in[0];
  p.wphi = (const __nv_bfloat16*)d_in[2];
  p.w1 = (const __nv_bfloat16*)d_in[5];
  p.b1 = (const __nv_bfloat16*)d_in[6];
  p.w2 = (const __nv_bfloat16*)d_in[7];
  p.b2 = (const __nv_bfloat16*)d_in[8];
  fused_kernel<<<NCTA, NTHREADS, SM_TOTAL>>>(tm_x, tm_act, tm_kv, tm_q, tm_u, tm_w1, tm_w2, ts_buf, ts_out, ts_u, tr_qkv, tr_wo, tm_h, ts_w, p);
}
```
